```python
import torch

def _softmax(x, axis=-1):
    return torch.softmax(x, dim=axis)
def _gelu(x):
    return torch.nn.functional.gelu(x, approximate="tanh")
def _silu(x):
    return torch.nn.functional.silu(x)
def _sigmoid(x):
    return torch.sigmoid(x)
def _layernorm(x, axis=-1, eps=1e-5):
    m = x.mean(dim=axis, keepdim=True)
    v = x.var(dim=axis, keepdim=True, unbiased=False)
    return (x - m) / torch.sqrt(v + eps)
def _scatter_add(tgt, idx, src, axis=0):
    return tgt.clone().index_add_(axis, idx, src)
def _segment_sum(src, seg, n):
    out = torch.zeros((n,) + src.shape[1:], dtype=src.dtype)
    return out.index_add_(0, seg, src)
def _pad(x, pw):
    flat = tuple(v for pair in reversed(pw) for v in pair)
    return torch.nn.functional.pad(x, flat)

kernel_name = 'sequential_preLN__sliding_block__moe_arch_mod__prompt'

def setup_inputs():

    _w = (lambda a: (lambda t: t.to(torch.bfloat16) if t.is_floating_point() else t)(torch.as_tensor(a)))
    def _A_setup():
        B, S, D = 1, 2048, 448
        return {
            "x": _w((lambda *s: torch.randn(*s, dtype=torch.bfloat16) * 0.05)(B, S, D)),
            "wqkv": _w((lambda *s: torch.randn(*s, dtype=torch.bfloat16) * 0.05)(D, 3 * D)),
            "wo": _w((lambda *s: torch.randn(*s, dtype=torch.bfloat16) * 0.05)(D, D)),
        }
    _A_in = _A_setup()

    def _B_setup():
        B, S, D, F, C = 1, 2048, 448, 1792, 2
        return {
            "x": _w((lambda *s: torch.randn(*s, dtype=torch.bfloat16) * 0.05)(B, S, D)),
            "w_r": _w((lambda *s: torch.randn(*s, dtype=torch.bfloat16) * 0.05)(D)),
            "w_gate": _w((lambda *s: torch.randn(*s, dtype=torch.bfloat16) * 0.05)(D, F)),
            "w_up": _w((lambda *s: torch.randn(*s, dtype=torch.bfloat16) * 0.05)(D, F)),
            "w_down": _w((lambda *s: torch.randn(*s, dtype=torch.bfloat16) * 0.05)(F, D)),
        }
    _B_in = _B_setup()

    return {
        "A_x": _A_in["x"],
        "A_wqkv": _A_in["wqkv"],
        "A_wo": _A_in["wo"],
        "B_x": _B_in["x"],
        "B_w_r": _B_in["w_r"],
        "B_w_gate": _B_in["w_gate"],
        "B_w_up": _B_in["w_up"],
        "B_w_down": _B_in["w_down"],
    }

def reference(A_x, A_wqkv, A_wo, B_x, B_w_r, B_w_gate, B_w_up, B_w_down):
    def _A_ref(x, wqkv, wo):
        B, S, D = x.shape
        H = 16; Dh = D // H; W = 256
        qkv = (lambda x, *d: x.permute(*d))((x @ wqkv).reshape(B, S, 3, H, Dh), 2, 0, 3, 1, 4)
        q, k, v = qkv[0], qkv[1], qkv[2]
        scores = torch.einsum("bhqd,bhkd->bhqk", q, k) * (Dh ** -0.5)
        idx = torch.arange(S)
        mask = (idx[:, None] - idx[None, :] >= 0) & (idx[:, None] - idx[None, :] < W)
        scores = torch.where(mask[None, None], scores, -1e9)
        p = _softmax(scores, axis=-1)
        o = torch.einsum("bhqk,bhkd->bhqd", p, v)
        return (lambda x, *d: x.permute(*d))(o, 0, 2, 1, 3).reshape(B, S, D) @ wo

    def _B_ref(x, w_r, w_gate, w_up, w_down):
        B, S, D = x.shape
        C = 2
        r = x @ w_r
        idx = torch.argsort(-r, axis=-1)[:, :C]
        idx_e = (lambda x, n, axis: torch.repeat_interleave(x, n, dim=axis))(idx.reshape(B, C, 1), D, axis=2)
        x_sel = (lambda x, i, axis: torch.take_along_dim(x, i, dim=axis))(x, idx_e, axis=1)
        g = _silu(x_sel @ w_gate)
        u = x_sel @ w_up
        y = (g * u) @ w_down
        r_sel = _sigmoid((lambda x, i, axis: torch.take_along_dim(x, i, dim=axis))(r, idx, axis=1))
        y = y * r_sel.reshape(B, C, 1)
        b_off = (torch.arange(B) * S).reshape(B, 1)
        flat_idx = (idx + b_off).reshape(B * C)
        zero = (x * 0.0).reshape(B * S, D)
        upd = _scatter_add(zero, flat_idx, y.reshape(B * C, D), axis=0)
        return x + upd.reshape(B, S, D)

    x = A_x
    h = x + _A_ref(_layernorm(x, axis=-1), A_wqkv, A_wo)
    h2 = h + _B_ref(_layernorm(h, axis=-1), B_w_r, B_w_gate, B_w_up, B_w_down)
    return h2
```

```cpp
#include <cuda_runtime.h>
#include <cuda_bf16.h>
#include <cuda.h>
#include <stdint.h>

#define OUTMODE 2
namespace {

constexpr int S_ = 2048, D_ = 448, F_ = 1792;
constexpr int NCTA = 128, NFFN = 112, NTHREADS = 384;
constexpr int SPIN_LIMIT = 1 << 18;

constexpr uint32_t R_K = 0;
constexpr uint32_t K_SLOT0 = 24576;
constexpr uint32_t R_V = 73728;
constexpr uint32_t X_SL = R_V + 32768;
constexpr uint32_t R_Q = 131072;
constexpr uint32_t R_M0 = 16384, R_M1 = X_SL + 16384;
constexpr uint32_t R_F = 188416;
constexpr uint32_t R_BAR = 231424;
constexpr uint32_t R_WR = R_BAR + 320;
constexpr uint32_t SMALL = R_Q + 49152;
constexpr uint32_t SMEM_BYTES = R_BAR + 1024;

__host__ __device__ constexpr uint32_t x_off(int c) { return c == 0 ? 57344 : 114688 + 16384 * c; }
__host__ __device__ constexpr uint32_t sec_off(int p) { return p == 0 ? R_K : (p == 1 ? R_V : R_Q); }
enum { B_X = 0, B_W = 7, B_FF = 19, B_KL, B_VL, B_KF, B_VF, B_WO, B_XS, B_KD0, B_KD1, B_VD0, B_VD1, B_QD0, B_QD1, B_E, B_XC = B_E + 3, B_WIN, B_COUNT };
__host__ __device__ constexpr int bar_count(int i) { return i < B_WO ? 1 : (i <= B_XS ? 2 : (i < B_XC ? 4 : 8)); }

struct __align__(1024) Scratch {
  uint4 kv[32][8][2][512];
  uint4 o[2][128][8][2][32];
  uint4 stats[128][8][16];
  uint4 part[NFFN][224];
  uint4 crow[32][2][8][8];
  uint4 rec[64][16];
  uint32_t epoch[8];
};
__device__ Scratch g_sc;

struct Params {
  const __nv_bfloat16* x; const __nv_bfloat16* wqkv; const __nv_bfloat16* wo; const __nv_bfloat16* wr;
  const __nv_bfloat16* wg; const __nv_bfloat16* wu; const __nv_bfloat16* wd;
  __nv_bfloat16* out; Scratch* sc;
};

__device__ __forceinline__ void wg_n56_t(float* d, uint32_t a0, uint32_t a1, uint32_t a2, uint32_t a3, uint64_t db, int scale_d) {
  asm volatile("{\n.reg .pred p;\nsetp.ne.b32 p, %33, 0;\n"
    "wgmma.mma_async.sync.aligned.m64n56k16.f32.bf16.bf16 "
    "{%0,%1,%2,%3,%4,%5,%6,%7,%8,%9,%10,%11,%12,%13,%14,%15,%16,%17,%18,%19,%20,%21,%22,%23,%24,%25,%26,%27"
    "}, {%28,%29,%30,%31}, %32, p, 1, 1, 1;\n}\n"
    : "+f"(d[0]), "+f"(d[1]), "+f"(d[2]), "+f"(d[3]), "+f"(d[4]), "+f"(d[5]), "+f"(d[6]), "+f"(d[7]),
      "+f"(d[8]), "+f"(d[9]), "+f"(d[10]), "+f"(d[11]), "+f"(d[12]), "+f"(d[13]), "+f"(d[14]), "+f"(d[15]),
      "+f"(d[16]), "+f"(d[17]), "+f"(d[18]), "+f"(d[19]), "+f"(d[20]), "+f"(d[21]), "+f"(d[22]), "+f"(d[23]),
      "+f"(d[24]), "+f"(d[25]), "+f"(d[26]), "+f"(d[27])
      : "r"(a0), "r"(a1), "r"(a2), "r"(a3), "l"(db), "r"(scale_d));
}
__device__ __forceinline__ void wg_n32_t(float* d, uint32_t a0, uint32_t a1, uint32_t a2, uint32_t a3, uint64_t db, int scale_d) {
  asm volatile("{\n.reg .pred p;\nsetp.ne.b32 p, %21, 0;\n"
    "wgmma.mma_async.sync.aligned.m64n32k16.f32.bf16.bf16 "
    "{%0,%1,%2,%3,%4,%5,%6,%7,%8,%9,%10,%11,%12,%13,%14,%15"
    "}, {%16,%17,%18,%19}, %20, p, 1, 1, 1;\n}\n"
    : "+f"(d[0]), "+f"(d[1]), "+f"(d[2]), "+f"(d[3]), "+f"(d[4]), "+f"(d[5]), "+f"(d[6]), "+f"(d[7]),
      "+f"(d[8]), "+f"(d[9]), "+f"(d[10]), "+f"(d[11]), "+f"(d[12]), "+f"(d[13]), "+f"(d[14]), "+f"(d[15])
      : "r"(a0), "r"(a1), "r"(a2), "r"(a3), "l"(db), "r"(scale_d));
}
__device__ __forceinline__ void wg_n64(float* d, uint32_t a0, uint32_t a1, uint32_t a2, uint32_t a3, uint64_t db, int scale_d) {
  asm volatile("{\n.reg .pred p;\nsetp.ne.b32 p, %37, 0;\n"
    "wgmma.mma_async.sync.aligned.m64n64k16.f32.bf16.bf16 "
    "{%0,%1,%2,%3,%4,%5,%6,%7,%8,%9,%10,%11,%12,%13,%14,%15,%16,%17,%18,%19,%20,%21,%22,%23,%24,%25,%26,%27,%28,%29,%30,%31"
    "}, {%32,%33,%34,%35}, %36, p, 1, 1, 0;\n}\n"
    : "+f"(d[0]), "+f"(d[1]), "+f"(d[2]), "+f"(d[3]), "+f"(d[4]), "+f"(d[5]), "+f"(d[6]), "+f"(d[7]),
      "+f"(d[8]), "+f"(d[9]), "+f"(d[10]), "+f"(d[11]), "+f"(d[12]), "+f"(d[13]), "+f"(d[14]), "+f"(d[15]),
      "+f"(d[16]), "+f"(d[17]), "+f"(d[18]), "+f"(d[19]), "+f"(d[20]), "+f"(d[21]), "+f"(d[22]), "+f"(d[23]),
      "+f"(d[24]), "+f"(d[25]), "+f"(d[26]), "+f"(d[27]), "+f"(d[28]), "+f"(d[29]), "+f"(d[30]), "+f"(d[31])
      : "r"(a0), "r"(a1), "r"(a2), "r"(a3), "l"(db), "r"(scale_d));
}
__device__ __forceinline__ void wg_n192(float* d, uint32_t a0, uint32_t a1, uint32_t a2, uint32_t a3, uint64_t db, int scale_d) {
  asm volatile("{\n.reg .pred p;\nsetp.ne.b32 p, %101, 0;\n"
    "wgmma.mma_async.sync.aligned.m64n192k16.f32.bf16.bf16 "
    "{%0,%1,%2,%3,%4,%5,%6,%7,%8,%9,%10,%11,%12,%13,%14,%15,%16,%17,%18,%19,%20,%21,%22,%23,%24,%25,%26,%27,%28,%29,%30,%31,"
    "%32,%33,%34,%35,%36,%37,%38,%39,%40,%41,%42,%43,%44,%45,%46,%47,%48,%49,%50,%51,%52,%53,%54,%55,%56,%57,%58,%59,%60,%61,%62,%63,"
    "%64,%65,%66,%67,%68,%69,%70,%71,%72,%73,%74,%75,%76,%77,%78,%79,%80,%81,%82,%83,%84,%85,%86,%87,%88,%89,%90,%91,%92,%93,%94,%95"
    "}, {%96,%97,%98,%99}, %100, p, 1, 1, 0;\n}\n"
    : "+f"(d[0]), "+f"(d[1]), "+f"(d[2]), "+f"(d[3]), "+f"(d[4]), "+f"(d[5]), "+f"(d[6]), "+f"(d[7]),
      "+f"(d[8]), "+f"(d[9]), "+f"(d[10]), "+f"(d[11]), "+f"(d[12]), "+f"(d[13]), "+f"(d[14]), "+f"(d[15]),
      "+f"(d[16]), "+f"(d[17]), "+f"(d[18]), "+f"(d[19]), "+f"(d[20]), "+f"(d[21]), "+f"(d[22]), "+f"(d[23]),
      "+f"(d[24]), "+f"(d[25]), "+f"(d[26]), "+f"(d[27]), "+f"(d[28]), "+f"(d[29]), "+f"(d[30]), "+f"(d[31]),
      "+f"(d[32]), "+f"(d[33]), "+f"(d[34]), "+f"(d[35]), "+f"(d[36]), "+f"(d[37]), "+f"(d[38]), "+f"(d[39]),
      "+f"(d[40]), "+f"(d[41]), "+f"(d[42]), "+f"(d[43]), "+f"(d[44]), "+f"(d[45]), "+f"(d[46]), "+f"(d[47]),
      "+f"(d[48]), "+f"(d[49]), "+f"(d[50]), "+f"(d[51]), "+f"(d[52]), "+f"(d[53]), "+f"(d[54]), "+f"(d[55]),
      "+f"(d[56]), "+f"(d[57]), "+f"(d[58]), "+f"(d[59]), "+f"(d[60]), "+f"(d[61]), "+f"(d[62]), "+f"(d[63]),
      "+f"(d[64]), "+f"(d[65]), "+f"(d[66]), "+f"(d[67]), "+f"(d[68]), "+f"(d[69]), "+f"(d[70]), "+f"(d[71]),
      "+f"(d[72]), "+f"(d[73]), "+f"(d[74]), "+f"(d[75]), "+f"(d[76]), "+f"(d[77]), "+f"(d[78]), "+f"(d[79]),
      "+f"(d[80]), "+f"(d[81]), "+f"(d[82]), "+f"(d[83]), "+f"(d[84]), "+f"(d[85]), "+f"(d[86]), "+f"(d[87]),
      "+f"(d[88]), "+f"(d[89]), "+f"(d[90]), "+f"(d[91]), "+f"(d[92]), "+f"(d[93]), "+f"(d[94]), "+f"(d[95])
      : "r"(a0), "r"(a1), "r"(a2), "r"(a3), "l"(db), "r"(scale_d));
}

__device__ __forceinline__ void wg_fence() { asm volatile("wgmma.fence.sync.aligned;" ::: "memory"); }
__device__ __forceinline__ void wg_commit() { asm volatile("wgmma.commit_group.sync.aligned;" ::: "memory"); }
__device__ __forceinline__ void wg_wait0() { asm volatile("wgmma.wait_group.sync.aligned 0;" ::: "memory"); }
__device__ __forceinline__ void wg_wait1() { asm volatile("wgmma.wait_group.sync.aligned 1;" ::: "memory"); }
template <int N> __device__ __forceinline__ void pin(float* d) {
#pragma unroll
  for (int i = 0; i < N; i++) asm volatile("" : "+f"(d[i])::"memory");
}
template <int N> __device__ __forceinline__ void pin(uint32_t* d) {
#pragma unroll
  for (int i = 0; i < N; i++) asm volatile("" : "+r"(d[i])::"memory");
}
__device__ __forceinline__ uint64_t mkdesc(uint32_t addr) {
  return (uint64_t)((addr & 0x3FFFF) >> 4) | (1ull << 16) | (64ull << 32) | (1ull << 62);
}
__device__ __forceinline__ void mbar_init(uint32_t a, int c) { asm volatile("mbarrier.init.shared::cta.b64 [%0], %1;" ::"r"(a), "r"(c) : "memory"); }
__device__ __forceinline__ void mbar_expect(uint32_t a, int b) { asm volatile("mbarrier.arrive.expect_tx.shared::cta.b64 _, [%0], %1;" ::"r"(a), "r"(b) : "memory"); }
__device__ __forceinline__ void mbar_arrive(uint32_t a) { asm volatile("mbarrier.arrive.shared::cta.b64 _, [%0];" ::"r"(a) : "memory"); }
__device__ __forceinline__ void mbar_arrive_if(bool on, uint32_t a) {
  asm volatile("{\n.reg .pred p;\nsetp.ne.u32 p, %1, 0;\n@p mbarrier.arrive.shared::cta.b64 _, [%0];\n}" ::"r"(a), "r"((uint32_t)on) : "memory");
}
__device__ __forceinline__ void mbar_wait(uint32_t a, uint32_t parity = 0) {
  asm volatile("{\n.reg .pred p;\n.reg .u32 n;\nmov.u32 n, 0;\n"
               "W_%=:\nmbarrier.try_wait.parity.shared::cta.b64 p, [%0], %1;\n@p bra D_%=;\n"
               "add.u32 n, n, 1;\nsetp.lt.u32 p, n, 1048576;\n@p bra W_%=;\nD_%=:\n}" ::"r"(a), "r"(parity) : "memory");
}
__device__ __forceinline__ void mbar_wait_tma(uint32_t a) {
  asm volatile("{\n.reg .pred p;\nW_%=:\nmbarrier.try_wait.parity.shared::cta.b64 p, [%0], 0;\n@!p bra W_%=;\n}" ::"r"(a) : "memory");
}
__device__ __forceinline__ void bar_sync(int id, int n) { asm volatile("bar.sync %0, %1;" ::"r"(id), "r"(n) : "memory"); }
__device__ __forceinline__ void bar_arrive(int id, int n) { asm volatile("bar.arrive %0, %1;" ::"r"(id), "r"(n) : "memory"); }
__device__ __forceinline__ void fence_async_smem() { asm volatile("fence.proxy.async.shared::cta;" ::: "memory"); }
__device__ __forceinline__ bool elect() {
  uint32_t p;
  asm volatile("{\n.reg .pred p;\nelect.sync _|p, 0xffffffff;\nselp.u32 %0, 1, 0, p;\n}" : "=r"(p));
  return p;
}
__device__ __forceinline__ void tma2d(uint32_t dst, const CUtensorMap* m, int c0, int c1, uint32_t bar) {
  asm volatile("cp.async.bulk.tensor.2d.shared::cluster.global.mbarrier::complete_tx::bytes [%0], [%1, {%3, %4}], [%2];"
               ::"r"(dst), "l"(m), "r"(bar), "r"(c0), "r"(c1) : "memory");
}
__device__ __forceinline__ void tma3d(uint32_t dst, const CUtensorMap* m, int c0, int c1, uint32_t bar) {
  asm volatile("cp.async.bulk.tensor.3d.shared::cluster.global.mbarrier::complete_tx::bytes [%0], [%1, {%3, %4, %5}], [%2];"
               ::"r"(dst), "l"(m), "r"(bar), "r"(c0), "r"(c1), "r"(0) : "memory");
}
__device__ __forceinline__ void bulk_load(uint32_t dst, const void* src, int bytes, uint32_t bar) {
  asm volatile("cp.async.bulk.shared::cluster.global.mbarrier::complete_tx::bytes [%0], [%1], %2, [%3];"
               ::"r"(dst), "l"(src), "r"(bytes), "r"(bar) : "memory");
}
__device__ __forceinline__ void bulk_store(void* dst, uint32_t src, int bytes) {
  asm volatile("cp.async.bulk.global.shared::cta.bulk_group [%0], [%1], %2;" ::"l"(dst), "r"(src), "r"(bytes) : "memory");
}
__device__ __forceinline__ uint32_t ld_relaxed(const uint32_t* p) {
  uint32_t v;
  asm volatile("ld.relaxed.gpu.global.u32 %0, [%1];" : "=r"(v) : "l"(p) : "memory");
  return v;
}
__device__ __forceinline__ void st_relaxed(uint32_t* p, uint32_t v) {
  asm volatile("st.relaxed.gpu.global.u32 [%0], %1;" ::"l"(p), "r"(v) : "memory");
}
__device__ __forceinline__ uint4 ld_ll(const void* p) {
  uint4 v;
  asm volatile("{\n.reg .b128 t;\n.reg .b64 lo, hi;\nld.relaxed.gpu.global.b128 t, [%4];\nmov.b128 {lo, hi}, t;\n"
               "mov.b64 {%0,%1}, lo;\nmov.b64 {%2,%3}, hi;\n}" : "=r"(v.x), "=r"(v.y), "=r"(v.z), "=r"(v.w) : "l"(p) : "memory");
  return v;
}
__device__ __forceinline__ void st_ll(void* p, uint32_t x, uint32_t y, uint32_t z, uint32_t w) {
  asm volatile("{\n.reg .b128 t;\n.reg .b64 lo, hi;\nmov.b64 lo, {%0,%1};\nmov.b64 hi, {%2,%3};\nmov.b128 t, {lo, hi};\n"
               "st.relaxed.gpu.global.b128 [%4], t;\n}" ::"r"(x), "r"(y), "r"(z), "r"(w), "l"(p) : "memory");
}
__device__ __forceinline__ void st_ll_if(bool on, void* p, uint32_t x, uint32_t y, uint32_t z, uint32_t w) {
  asm volatile("{\n.reg .pred p;\nsetp.ne.u32 p, %5, 0;\n@p st.relaxed.gpu.global.v4.u32 [%4], {%0,%1,%2,%3};\n}"
               ::"r"(x), "r"(y), "r"(z), "r"(w), "l"(p), "r"((uint32_t)on) : "memory");
}
template <class T> __device__ __forceinline__ void pinp(T*& p) { asm volatile("" : "+l"(p)); }
__device__ __forceinline__ uint32_t sel(bool c, uint32_t a, uint32_t b) {
  uint32_t r;
  asm("{\n.reg .pred p;\nsetp.ne.u32 p, %3, 0;\nselp.b32 %0, %1, %2, p;\n}" : "=r"(r) : "r"(a), "r"(b), "r"((uint32_t)c));
  return r;
}
__device__ __forceinline__ uint32_t tag_lo(uint32_t v, uint32_t tag_hi) { return __byte_perm(v, tag_hi, 0x7610); }
__device__ __forceinline__ uint32_t tag_up(uint32_t v, uint32_t tag_hi) { return __byte_perm(v, tag_hi, 0x7632); }
__device__ __forceinline__ uint32_t untag(uint32_t a, uint32_t b) { return __byte_perm(a, b, 0x5410); }
__device__ __forceinline__ void stsm4(uint32_t a, uint32_t r0, uint32_t r1, uint32_t r2, uint32_t r3) {
  asm volatile("stmatrix.sync.aligned.m8n8.x4.shared.b16 [%0], {%1,%2,%3,%4};" ::"r"(a), "r"(r0), "r"(r1), "r"(r2), "r"(r3) : "memory");
}
__device__ __forceinline__ void ldsm4(uint32_t a, uint32_t* r) {
  asm volatile("ldmatrix.sync.aligned.m8n8.x4.shared.b16 {%0,%1,%2,%3}, [%4];" : "=r"(r[0]), "=r"(r[1]), "=r"(r[2]), "=r"(r[3]) : "r"(a) : "memory");
}
__device__ __forceinline__ void ldsm4t(uint32_t a, uint32_t* r) {
  asm volatile("ldmatrix.sync.aligned.m8n8.x4.trans.shared.b16 {%0,%1,%2,%3}, [%4];" : "=r"(r[0]), "=r"(r[1]), "=r"(r[2]), "=r"(r[3]) : "r"(a) : "memory");
}
__device__ __forceinline__ void mma16816(float* c, uint32_t a0, uint32_t a1, uint32_t a2, uint32_t a3, uint32_t b0, uint32_t b1) {
  asm("mma.sync.aligned.m16n8k16.row.col.f32.bf16.bf16.f32 {%0,%1,%2,%3}, {%4,%5,%6,%7}, {%8,%9}, {%0,%1,%2,%3};"
      : "+f"(c[0]), "+f"(c[1]), "+f"(c[2]), "+f"(c[3]) : "r"(a0), "r"(a1), "r"(a2), "r"(a3), "r"(b0), "r"(b1));
}
__device__ __forceinline__ void mma1688(float* c, uint32_t a0, uint32_t a1, uint32_t b0) {
  asm("mma.sync.aligned.m16n8k8.row.col.f32.bf16.bf16.f32 {%0,%1,%2,%3}, {%4,%5}, {%6}, {%0,%1,%2,%3};"
      : "+f"(c[0]), "+f"(c[1]), "+f"(c[2]), "+f"(c[3]) : "r"(a0), "r"(a1), "r"(b0));
}
__device__ __forceinline__ uint32_t pack(float lo, float hi) {
  uint32_t r;
  asm("cvt.rn.bf16x2.f32 %0, %1, %2;" : "=r"(r) : "f"(hi), "f"(lo));
  return r;
}
__device__ __forceinline__ float lo_f(uint32_t v) { return __uint_as_float(v << 16); }
__device__ __forceinline__ float hi_f(uint32_t v) { return __uint_as_float(v & 0xffff0000u); }
__device__ __forceinline__ float rbf(float v) { return hi_f(pack(0.f, v)); }
__device__ __forceinline__ uint32_t sub_bf2(uint32_t a, uint32_t b) {
  uint32_t r;
  asm("sub.rn.bf16x2 %0, %1, %2;" : "=r"(r) : "r"(a), "r"(b));
  return r;
}
__device__ __forceinline__ uint32_t mul_bf2(uint32_t a, uint32_t b) {
  uint32_t r;
  asm("mul.rn.bf16x2 %0, %1, %2;" : "=r"(r) : "r"(a), "r"(b));
  return r;
}
__device__ __forceinline__ uint32_t fma_bf2(uint32_t a, uint32_t b, uint32_t c) {
  uint32_t r;
  asm("fma.rn.bf16x2 %0, %1, %2, %3;" : "=r"(r) : "r"(a), "r"(b), "r"(c));
  return r;
}
__device__ __forceinline__ uint32_t add_bf2(uint32_t a, uint32_t b) {
  uint32_t r;
  asm("add.rn.bf16x2 %0, %1, %2;" : "=r"(r) : "r"(a), "r"(b));
  return r;
}
__device__ __forceinline__ float ex2(float x) {
  float r;
  asm("ex2.approx.ftz.f32 %0, %1;" : "=f"(r) : "f"(x));
  return r;
}
__device__ __forceinline__ uint32_t shfl_x(uint32_t v, int m) { return __shfl_xor_sync(0xffffffffu, v, m); }
__device__ __forceinline__ float shfl_x(float v, int m) { return __shfl_xor_sync(0xffffffffu, v, m); }
__device__ __forceinline__ float quad_sum(float v) { v += shfl_x(v, 1); return v + shfl_x(v, 2); }
template <int N> __device__ __forceinline__ void acc_max(const float* s, float& m0, float& m1, float& m2, float& m3) {
#pragma unroll
  for (int i = 0; i < N; i += 8) {
    m0 = fmaxf(m0, fmaxf(s[i], s[i + 1])); m1 = fmaxf(m1, fmaxf(s[i + 2], s[i + 3]));
    m2 = fmaxf(m2, fmaxf(s[i + 4], s[i + 5])); m3 = fmaxf(m3, fmaxf(s[i + 6], s[i + 7]));
  }
}
__device__ __forceinline__ float rcp(float x) {
  float r;
  asm("rcp.approx.ftz.f32 %0, %1;" : "=f"(r) : "f"(x));
  return r;
}
__device__ __forceinline__ uint32_t to_key(float f, uint32_t inv_tok) {
  const uint32_t u = __float_as_uint(f);
  return (f == f ? (u ^ ((uint32_t)((int)u >> 31) | 0x80000000u)) & 0xfffff800u : 0x800u) | inv_tok;
}
__device__ __forceinline__ float key_score(uint32_t k) { return __uint_as_float(k ^ ((uint32_t)((int)~k >> 31) | 0x80000000u)); }
__device__ __forceinline__ uint32_t key_token(uint32_t k) { return ~k & 2047u; }
__device__ __forceinline__ void top2(uint32_t key, uint32_t& k1, uint32_t& k2) {
  k1 = __reduce_max_sync(0xffffffffu, key);
  k2 = __reduce_max_sync(0xffffffffu, key == k1 ? 0u : key);
}
__device__ __forceinline__ uint32_t keep(uint32_t v) { return __shfl_sync(0xffffffffu, v, threadIdx.x & 31); }
#define OFF(member) ((uint32_t)((const char*)&((Scratch*)0)->member - (const char*)0))

#define TSH(a, b, c)
#define TSA(a, b, c)
#define TSB(a, b)
#define TS(slot, i)
#define TSL(slot, i)
#define TSV(slot, i, v)
#define TSDUMP()

__global__ void __launch_bounds__(NTHREADS, 1)
fused_block_kernel(const Params P, const __grid_constant__ CUtensorMap tm_x, const __grid_constant__ CUtensorMap tm_w,
                   const __grid_constant__ CUtensorMap tm_wo,
                   const __grid_constant__ CUtensorMap tm_g,
                   const __grid_constant__ CUtensorMap tm_u, const __grid_constant__ CUtensorMap tm_d) {
  extern __shared__ __align__(1024) unsigned char smem[];
  const uint32_t sb = (uint32_t)__cvta_generic_to_shared(smem);
  const int tid = threadIdx.x, lane = tid & 31;
  const int warp = __shfl_sync(0xffffffffu, tid >> 5, 0);
  const int cta = blockIdx.x, m = (cta >> 4) * 2 + (cta & 1), g = (cta >> 1) & 7;
  const int col0 = (56 * g) & ~15;
  const int q = lane & 3, r8 = lane >> 2;
  const uint32_t swz = (lane & 7) * 128 + ((lane >> 3) ^ (lane & 7)) * 16;
  Scratch* const sc = P.sc;
  auto bar = [&](int i) { return sb + R_BAR + 8 * i; };

  if (warp >= 8) {
    asm volatile("setmaxnreg.dec.sync.aligned.u32 56;");
    const int j = warp - 8;
    if (j == 0 && elect()) {
#pragma unroll
      for (int i = B_X; i < B_W; i++) mbar_init(bar(i), 1);
      asm volatile("fence.mbarrier_init.release.cluster;" ::: "memory");
#pragma unroll 1
      for (int c = 0; c < 7; c++) {
        mbar_expect(bar(B_X + c), 16384);
        tma2d(sb + x_off(c), &tm_x, 64 * c, 128 * m, bar(B_X + c));
      }
    }
    if (j == 1 && elect()) {
      asm volatile("prefetch.tensormap [%0];" ::"l"(&tm_w) : "memory");
#pragma unroll
      for (int i = B_W; i < B_COUNT; i++) mbar_init(bar(i), bar_count(i));
      asm volatile("fence.mbarrier_init.release.cluster;" ::: "memory");
    }
    bar_sync(0, NTHREADS);
    if (j == 0) {
      if (elect()) {
#pragma unroll 1
        for (int c = 0; c < 12; c++) {
          if (c == 8) mbar_wait_tma(bar(B_XC));
          if (c >= 10) {
            mbar_wait_tma(bar(B_KD0 + c - 10));
            bulk_store(&sc->kv[2 * m + c - 10][g][0][0], sb + K_SLOT0 + (c - 6) * 8192, 8192);
          }
          mbar_expect(bar(B_W + c), 14336);
          tma2d(sb + sec_off(c >> 2) + 14336 * (c & 3), &tm_w, col0 + (c >= 8 ? 0 : 448 + 448 * (c >> 2)), 112 * (c & 3), bar(B_W + c));
          if (c == 7) TSL(2, 0);
        }
#pragma unroll 1
        for (int w = 0; w < 2; w++) {
          mbar_wait_tma(bar(B_VD0 + w));
          bulk_store(&sc->kv[2 * m + w][g][1][0], sb + R_K + w * 8192, 8192);
        }
        asm volatile("cp.async.bulk.commit_group;" ::: "memory");
        TSL(2, 10);
        mbar_wait_tma(bar(B_QD0)); mbar_wait_tma(bar(B_QD1));
        mbar_wait(bar(B_VF));
        mbar_expect(bar(B_WO), 49152);
        tma3d(sb + R_Q, &tm_wo, col0, 0, bar(B_WO)); tma3d(sb + R_Q + 24576, &tm_wo, col0, 32, bar(B_WO));
        mbar_expect(bar(B_XS), 16384);
        tma2d(sb + X_SL, &tm_x, col0, 128 * m, bar(B_XS));
        if (cta < NFFN) {
          mbar_expect(bar(B_FF), 43008);
#pragma unroll 1
          for (int i = 0; i < 2; i++) {
            tma2d(sb + R_F + 7168 * i, &tm_g, 16 * cta, 224 * i, bar(B_FF));
            tma2d(sb + R_F + 14336 + 7168 * i, &tm_u, 16 * cta, 224 * i, bar(B_FF));
          }
          tma3d(sb + R_F + 28672, &tm_d, 0, 16 * cta, bar(B_FF));
        }
        asm volatile("cp.async.bulk.wait_group.read 0;" ::: "memory");
        TSL(2, 3);
      }
    } else if (j < 3) {
      const int kv = j - 1, first = max(4 - 2 * m, 0);
      const uint32_t tag = ((ld_relaxed(&sc->epoch[0]) + 1) & 127) << 16;
      const uint4* src = &sc->kv[2 * m - 4 + max(q, first)][g][kv][0];
      const uint32_t dst = kv ? R_V : K_SLOT0;
      int spins = 0;
#pragma unroll 1
      while (first < 4 && __any_sync(0xffffffffu, (ld_relaxed((const uint32_t*)src + 2034) ^ tag) > 0xffffu) && ++spins < SPIN_LIMIT) {}
      if (lane == 0) TSL(2, 4 + 2 * kv);
      mbar_wait(bar(B_KD0 + 2 * kv)); mbar_wait(bar(B_KD1 + 2 * kv));
      const uint32_t toff = dst + lane * 128 + ((lane & 7) ^ 3) * 16 + 8;
      uint32_t bad, kmax, parity = 0;
#pragma unroll 1
      do {
        if (lane == 0) mbar_expect(bar(B_KL + kv), (4 - first) * 8192);
        __syncwarp();
        if (lane < 4 && lane >= first) bulk_load(sb + dst + lane * 8192, src, 8192, bar(B_KL + kv));
        mbar_wait(bar(B_KL + kv), parity);
        parity ^= 1;
        bad = 0; kmax = 0;
#pragma unroll
        for (int i = 0; i < 12; i++) {
          const uint32_t u = *(const volatile uint32_t*)(smem + toff + 4 + ((kv && i >= 8) ? 7 : max(i, 2 * first)) * 4096);
          bad |= u ^ tag; kmax = max(kmax, u & 0xffffu);
        }
        if (first == 4 && kv) bad = 0;
      } while (__any_sync(0xffffffffu, bad > 0xffffu) && ++spins < SPIN_LIMIT);
      if (lane == 0) TSL(2, 5 + 2 * kv);
      if (kv == 0) {
#pragma unroll 1
        for (int i = 0; i < 2 * first; i++) {
          *(uint32_t*)(smem + toff + i * 4096) = 0xff80u;
          *(uint32_t*)(smem + (toff ^ 0x40) - 8 + i * 4096) = 0xff80u;
        }
        if (first) fence_async_smem();
        kmax = __reduce_max_sync(0xffffffffu, kmax);
        if (lane == 0) *(uint2*)(smem + R_WR + 128) = make_uint2(kmax << 16, 0u);
      }
      __syncwarp();
      if (lane == 0) { mbar_arrive(bar(B_KF + kv)); TSL(2, 1 + kv); }
    } else {
      mbar_wait_tma(bar(B_X + 6));
      if (cta < NFFN && lane < 28) {
        const char* wrow = (const char*)P.wqkv + (4 * cta + lane / 7) * 2688 + (lane % 7) * 128;
        asm volatile("prefetch.global.L2 [%0];" ::"l"(wrow + 1792));
        asm volatile("prefetch.global.L2 [%0];" ::"l"(wrow));
        asm volatile("prefetch.global.L2 [%0];" ::"l"((const char*)P.wo + cta * 3584 + lane * 128));
      }
      float ws = 0.f;
#pragma unroll
      for (int i = 0; i < 7; i++) { const uint32_t v = __ldg((const uint32_t*)P.wr + 32 * i + lane); ws += lo_f(v) + hi_f(v); }
      const uint32_t own = __ldg((const uint32_t*)P.wr + 28 * g + min(lane, 27));
#pragma unroll
      for (int i = 1; i < 32; i <<= 1) ws += shfl_x(ws, i);
      ((uint32_t*)(smem + R_WR))[lane] = lane < 28 ? own : __float_as_uint(ws);
      __syncwarp();
      if (lane == 0) mbar_arrive(bar(B_XS));
      mbar_wait_tma(bar(B_W + 7));
#pragma unroll 1
      for (int i = lane; i < 98; i += 32) {
        asm volatile("prefetch.global.L2 [%0];" ::"l"((const char*)P.wg + cta * 12544 + i * 128));
        asm volatile("prefetch.global.L2 [%0];" ::"l"((const char*)P.wu + cta * 12544 + i * 128));
        asm volatile("prefetch.global.L2 [%0];" ::"l"((const char*)P.wd + cta * 12544 + i * 128));
      }
      mbar_wait(bar(B_VF)); mbar_wait_tma(bar(B_QD0)); mbar_wait_tma(bar(B_QD1));
#pragma unroll 1
      for (int i = 0; i < 32; i++) {
        const int row = (lane >> 3) + 4 * (i & 1), hh = i >> 4;
        const int src = 56 * ((i >> 1) & 7) + ((row & 1) ? 32 * hh + 8 + row : 24 + 4 * hh + (row >> 1));
        asm volatile("cp.async.cg.shared.global [%0], [%1], 16;" ::"r"(sb + (hh ? R_M1 - 8192 : R_M0) + (i >> 1) * 1024 + row * 128 + ((lane ^ row) & 7) * 16),
                     "l"((const char*)P.wo + src * 896 + col0 * 2 + (lane & 7) * 16) : "memory");
      }
      asm volatile("cp.async.wait_all;" ::: "memory");
      fence_async_smem();
      __syncwarp();
      if (lane == 0) mbar_arrive(bar(B_WO));
    }
    __syncwarp();
    mbar_wait(bar(B_WIN));
    const uint2 win = *(const uint2*)(smem + R_WR + 136);
    char* const op = (char*)P.out + (128 * m + 32 * j) * 896 + 112 * g + 16 * lane;
#pragma unroll
    for (int i = 0; i < 7; i++) {
      const int id = lane + 32 * i, r = (id * 9363) >> 16;
      const uint4 v = *(const uint4*)(smem + X_SL + 3584 * j + 16 * id);
      const uint32_t tok = 128 * m + 32 * j + r;
      if (OUTMODE != 0 && tok != win.x && tok != win.y) *(uint4*)(op + r * 784 + 512 * i) = v;
    }
    return;
  }

  asm volatile("setmaxnreg.inc.sync.aligned.u32 224;");
  const int w = warp >> 2, wi = warp & 3;
  const bool bsel = r8 & 1;
  const int tile = 8 * m + warp, row0 = 16 * tile;
  const int dsrc = (lane & 28) | (r8 >> 1);
  uint32_t A[112];
  const uint32_t epoch = ld_relaxed(&sc->epoch[0]) + 1, tag_hi = epoch << 16;
  float rstd0, rstd1;
  const uint32_t otag = keep((epoch & 127) << 16);
  char* const scb = (char*)sc;
  {
    const uint32_t e = epoch - 1;
    st_ll_if(lane >= 24, &sc->o[1][tile][g][1][lane], (e & 127) << 16, 0, 0, 0);
    st_ll_if(q == 0, &sc->stats[tile][g][r8], 0, 0, 0, e);
    st_ll_if(q == 0, &sc->stats[tile][g][r8 + 8], 0, 0, 0, e);
    st_ll_if(tid < 8, &sc->rec[8 * g + (tid & 7)][m], 0, 0, 0, e);
    st_ll_if(warp < 7 && cta < NFFN, &sc->part[cta][32 * warp + 8 * q + r8], 0, 0, 0, e);
  }
  bar_sync(0, NTHREADS);
  TS(w, 0);
  {
    float c0[4] = {0.f, 0.f, 0.f, 0.f}, c1[4] = {0.f, 0.f, 0.f, 0.f}, c2[4] = {0.f, 0.f, 0.f, 0.f}, c3[4] = {0.f, 0.f, 0.f, 0.f}, c4[4] = {0.f, 0.f, 0.f, 0.f};
    const uint32_t xa = sb + (16 * warp + (lane & 15)) * 128 + ((lane >> 4) ^ (lane & 7)) * 16;
#pragma unroll
    for (int L = 0; L < 7; L++) {
      mbar_wait_tma(bar(B_X + L));
      if (L == 0) TS(w, 28);
      if (L == 6) TS(w, 29);
#pragma unroll
      for (int t = 0; t < 4; t++) ldsm4((xa ^ (32 * t)) + x_off(L), A + 16 * L + 4 * t);
#pragma unroll
      for (int t = 0; t < 4; t++) {
        const uint32_t* a = A + 16 * L + 4 * t;
        mma16816(c0, a[0], a[1], a[2], a[3], 0x3f803f80u, 0x3f803f80u);
        mma1688(c1, a[0], a[1], a[0]); mma1688(c2, a[0], a[1], a[1]);
        mma1688(c3, a[2], a[3], a[2]); mma1688(c4, a[2], a[3], a[3]);
      }
    }
    const float mu0 = c0[0] * (1.f / D_), mu1 = c0[2] * (1.f / D_);
    uint32_t mb[2] = {pack(mu0, mu0), pack(mu1, mu1)};
    pin<2>(mb);
    __syncwarp();
    if (lane == 0) mbar_arrive(bar(B_XC));
#pragma unroll
    for (int i = 0; i < 112; i++) A[i] = sub_bf2(A[i], mb[i & 1]);
    const float q0 = __shfl_sync(0xffffffffu, bsel ? c1[1] + c3[1] : c1[0] + c3[0], dsrc);
    const float q1 = __shfl_sync(0xffffffffu, bsel ? c2[3] + c4[3] : c2[2] + c4[2], dsrc);
    rstd0 = rsqrtf(fmaxf(fmaf(q0, 1.f / D_, -mu0 * mu0), 0.f) + 1e-5f);
    rstd1 = rsqrtf(fmaxf(fmaf(q1, 1.f / D_, -mu1 * mu1), 0.f) + 1e-5f);
    TS(w, 1);
  }

  uint32_t pk[14], t0[2], t1[2];
  uint32_t nn;
  {
    float acc[28];
#pragma unroll
    for (int i = 0; i < 28; i++) acc[i] = 0.f;
#pragma unroll 1
    for (int p = 0; p < 3; p++) {
      if (p + w > 0) bar_sync(1 + w, 256);
      const uint64_t db = mkdesc(sb + sec_off(p) + (g & 1) * 16);
      pin<28>(acc);
#pragma unroll
      for (int c = 0; c < 4; c++) {
        mbar_wait_tma(bar(B_W + 4 * p + c));
        pin<28>(A + 28 * c);
        wg_fence();
#pragma unroll
        for (int t = 7 * c; t < 7 * c + 7; t++) wg_n56_t(acc, A[4 * t], A[4 * t + 1], A[4 * t + 2], A[4 * t + 3], db + t * 128, t > 0);
        wg_commit();
      }
      if (p + w < 3) bar_arrive(2 - w, 256);
      TSA(w, 2 + 3 * p, 2);
      wg_wait0();
      pin<28>(acc);
      TSA(w, 3 + 3 * p, 3);
      const float qs = p == 2 ? 0.18898223650461362f * 1.4426950408889634f : 1.f;
      const float f0 = rstd0 * qs, f1 = rstd1 * qs;
      const uint32_t padv = sel(p == 2, 0x3f803f80u, otag | (p * 0x3f80u));
#pragma unroll
      for (int j = 0; j < 7; j++) {
        pk[j] = pack(acc[4 * j] * f0, acc[4 * j + 1] * f0);
        pk[7 + j] = pack(acc[4 * j + 2] * f1, acc[4 * j + 3] * f1);
      }
      uint32_t n0 = mul_bf2(pk[0], pk[0]), n1 = mul_bf2(pk[7], pk[7]);
#pragma unroll
      for (int j = 1; j < 7; j++) { n0 = fma_bf2(pk[j], pk[j], n0); n1 = fma_bf2(pk[7 + j], pk[7 + j], n1); }
      nn = add_bf2(__byte_perm(n0, n1, 0x5410), __byte_perm(n0, n1, 0x7632));
      nn = add_bf2(nn, shfl_x(nn, 1)); nn = add_bf2(nn, shfl_x(nn, 2));
      asm("min.bf16x2 %0, %0, %1;" : "+r"(nn) : "r"(0x7f7f7f7fu));
#pragma unroll
      for (int h = 0; h < 2; h++) {
        const uint32_t pad3 = __byte_perm(nn, otag, p == 2 ? 0x5454 : (h ? 0x7632 : 0x7610));
        t0[h] = sel(q < 2, pk[7 * h + 3], sel(q == 3, pad3, padv));
        t1[h] = sel(q < 2, padv, pk[7 * h + 3]);
      }
      if (p < 2) {
        mbar_wait_tma(bar(p ? B_KD1 : B_XC));
        const uint32_t base = sb + (p ? R_K : K_SLOT0 + 32768) + 2048 * warp + swz;
#pragma unroll
        for (int h = 0; h < 2; h++) {
          const uint32_t* k = pk + 7 * h;
          stsm4(base + h * 1024, k[0], k[1], k[2], t0[h]);
          stsm4((base ^ 64) + h * 1024, k[4], k[5], k[6], t1[h]);
        }
        fence_async_smem();
      }
      __syncwarp();
      if (lane == 0) mbar_arrive(bar(B_KD0 + 2 * p + w));
      TSA(w, 4 + 3 * p, 4);
    }
  }
  float hv[28];
  uint32_t xs[16], bw[7], o_so, o_si, o_cp, o_rp, inv_tok;
  float wsum;
  const int rloc = r8 + 4 * (q & 2);
  {
    const uint4* const ip = (const uint4*)(scb + keep(OFF(o[0][tile][0][0][lane])));
    uint4* op = (uint4*)ip + 64 * g;
    {
      uint32_t qa[8] = {pk[0], pk[7], pk[1], pk[8], pk[2], pk[9], t0[0], t0[1]};
      const int dg = 16 * wi + r8 - 2 * q;
      uint64_t dk = mkdesc(sb + K_SLOT0 + w * 8192), dv_rem = mkdesc(sb + R_V + w * 8192), dv_own = mkdesc(sb + R_K);
      mbar_wait(bar(B_KF));
      uint32_t need_max;
      asm volatile("{\n.reg .pred p, r;\nsetp.le.f32 p, %1, 0f45BB8000;\nbar.red.and.pred r, %2, 128, p;\nselp.u32 %0, 0, 1, r;\n}"
                   : "=r"(need_max) : "f"(fmaxf(lo_f(nn), hi_f(nn)) * ((const volatile float*)(smem + R_WR))[32]), "r"(4 + w) : "memory");
      TS(w, 11);
      float o[16];
      uint32_t pp[80];
#pragma unroll 1
      for (int hh = 0;; hh++) {
        float s[128], sd[32];
        pin<8>(qa);
        wg_fence();
        wg_n64(s, qa[0], qa[1], qa[2], qa[3], dk, 0);
        wg_n64(s, qa[4], qa[5], qa[6], qa[7], dk + 2, 1);
        wg_n64(sd, qa[0], qa[1], qa[2], qa[3], dk + 2048, 0);
        wg_n64(sd, qa[4], qa[5], qa[6], qa[7], dk + 2050, 1);
        wg_commit();
        wg_n192(s + 32, qa[0], qa[1], qa[2], qa[3], dk + 512, 0);
        wg_n192(s + 32, qa[4], qa[5], qa[6], qa[7], dk + 514, 1);
        wg_commit();
        wg_wait1();
        pin<32>(s); pin<32>(sd);
#pragma unroll
        for (int i = 0; i < 32; i++) sd[i] = (8 * ((i >> 2) - ((i >> 1) & 1)) + (i & 1) <= dg) ? sd[i] : s[i];
        pin<32>(sd);
        wg_wait0();
        pin<96>(s + 32);
        float m0 = 0.f, m1 = 0.f;
        if (need_max) {
          float m2 = fmaxf(sd[4], sd[5]), m3 = fmaxf(sd[6], sd[7]);
          m0 = fmaxf(sd[0], sd[1]); m1 = fmaxf(sd[2], sd[3]);
          acc_max<24>(sd + 8, m0, m1, m2, m3);
          acc_max<96>(s + 32, m0, m1, m2, m3);
          m0 = fmaxf(m0, m2); m1 = fmaxf(m1, m3);
          m0 = fmaxf(m0, shfl_x(m0, 1)); m1 = fmaxf(m1, shfl_x(m1, 1));
          m0 = fmaxf(m0, shfl_x(m0, 2)); m1 = fmaxf(m1, shfl_x(m1, 2));
        }
        if (hh + w > 0) mbar_wait_tma(bar(B_E + 2 * hh + w - 1));
        {
          const float zero = ((const volatile float*)(smem + R_WR))[33];
          m0 += zero; m1 += zero;
        }
        TSH(w, 13 + 4 * hh, 13);
        uint32_t dep = 0;
#pragma unroll
        for (int i = 0; i < 64; i++) {
          const float* sp = i < 16 ? sd : s;
          const float mm = (i & 1) ? m1 : m0;
          pp[i] = pack(ex2(sp[2 * i] - mm), ex2(sp[2 * i + 1] - mm));
          if ((i & 1) && i < 56) asm volatile("lop3.b32 %0, %0, %1, %2, 0xfe;" : "+r"(dep) : "r"(pp[i - 1]), "r"(pp[i]));
          if (i == 55) mbar_arrive_if(hh + w < 2 && lane == 0, bar(B_E + 2 * hh + w) + (dep >> 31));
        }
        pin<64>(pp);
        TSH(w, 14 + 4 * hh, 14);
        mbar_wait(bar(B_VF));
        wg_fence();
#pragma unroll
        for (int b = 1; b < 4; b++) {
          const uint64_t dv = (b == 3 && w == 1) ? dv_own : dv_rem + b * 512;
#pragma unroll
          for (int k = 0; k < 4; k++) wg_n32_t(o, pp[16 * b + 4 * k], pp[16 * b + 4 * k + 1], pp[16 * b + 4 * k + 2], pp[16 * b + 4 * k + 3], dv + k * 128, b + k > 1);
        }
        wg_commit();
#pragma unroll
        for (int i = 0; i < 16; i++) {
          const uint32_t mk = __funnelshift_lc(0xffffffffu, 0u, __viaddmax_s32(16 * dg, 16 - 128 * ((i >> 1) - (i & 1)), 0));
          pp[64 + i] = pp[i] & mk;
          pp[i] &= ~mk;
        }
        pin<16>(pp); pin<16>(pp + 64);
        wg_fence();
#pragma unroll
        for (int k = 0; k < 4; k++) wg_n32_t(o, pp[64 + 4 * k], pp[65 + 4 * k], pp[66 + 4 * k], pp[67 + 4 * k], dv_own + w * 512 + k * 128, 1);
#pragma unroll
        for (int k = 0; k < 4; k++) wg_n32_t(o, pp[4 * k], pp[4 * k + 1], pp[4 * k + 2], pp[4 * k + 3], dv_rem + k * 128, 1);
        wg_commit();
        wg_wait0();
        pin<16>(o);
        const int lsrc = (lane & 28) | (2 - 2 * hh);
        const float l0 = rcp(__shfl_sync(0xffffffffu, o[12], lsrc)), l1 = rcp(__shfl_sync(0xffffffffu, o[14], lsrc));
        uint32_t u[8];
#pragma unroll
        for (int j = 0; j < 4; j++) {
          u[j] = pack(o[4 * j] * l0, o[4 * j + 1] * l0);
          u[4 + j] = pack(o[4 * j + 2] * l1, o[4 * j + 3] * l1);
        }
        const int xsrc = (lane & 28) | (2 * hh + (q >> 1));
        const uint32_t x0 = __shfl_sync(0xffffffffu, u[3], xsrc), x1 = __shfl_sync(0xffffffffu, u[7], xsrc), ps = 0x7610 + (q & 1) * 0x22;
        st_ll(op, u[0], u[4], u[1], tag_lo(u[5], otag));
        st_ll(op + 32, __byte_perm(x0, otag, ps), __byte_perm(x1, u[5], ps), u[2], u[6]);
        TSH(w, 15 + 4 * hh, 15);
        if (hh) break;
        op += 128 * 8 * 64;
        qa[0] = pk[4]; qa[1] = pk[11]; qa[2] = pk[5]; qa[3] = pk[12]; qa[4] = pk[6]; qa[5] = pk[13]; qa[6] = t1[0]; qa[7] = t1[1];
        dk += 4; dv_rem += 4; dv_own += 4;
      }
    }
    int spins = 0;
    uint32_t redo;
#pragma unroll 1
    do {
      uint4 v[32];
      TSB(w, 2);
#pragma unroll
      for (int i = 0; i < 16; i++) v[i] = ld_ll(ip + 32 * i);
      const uint32_t* sp = &sc->o[1][tile][lane & 7][1][31].x;
      uint32_t sent = ld_relaxed(sp);
      mbar_wait(bar(B_XS));
      {
        const uint32_t xa = sb + X_SL + (16 * warp + (lane & 7)) * 128 + ((((lane >> 3) + (g & 1)) ^ lane) & 7) * 16;
        ldsm4(xa, xs); ldsm4(xa ^ 64, xs + 4); ldsm4(xa + 1024, xs + 8); ldsm4((xa ^ 64) + 1024, xs + 12);
      }
#pragma unroll
      for (int j = 0; j < 7; j++) bw[j] = sel(r8 == 0, 0x3f803f80u, ((const volatile uint32_t*)(smem + R_WR))[4 * j + q]);
      wsum = ((const volatile float*)(smem + R_WR))[28];
      o_so = keep(OFF(stats[tile][g][r8])); o_si = keep(OFF(stats[tile][4 * (q & 1)][rloc]));
      o_cp = keep(OFF(crow[2 * m][0][g][q])); o_rp = keep(OFF(rec[8 * g + (tid & 7)][m]));
      inv_tok = keep(2047 - row0 - rloc);
      const uint64_t db = mkdesc(__shfl_sync(0xffffffffu, sb + (g & 1) * 16 + (sent & 0), 0));
      TSB(w, 3);
#pragma unroll 1
      while (__any_sync(0xffffffffu, (sent ^ otag) > 0xffffu) && ++spins < SPIN_LIMIT) sent = ld_relaxed(sp);
      TS(w, 12);
#pragma unroll
      for (int i = 0; i < 16; i++) v[16 + i] = ld_ll(ip + 65536 + 32 * i);
      mbar_wait(bar(B_WO));
      TSB(w, 4);
#pragma unroll
      for (int i = 0; i < 16; i++) {
        const int st = i >> 3, gg = i & 7, mo = (st ? R_M1 : R_M0) + gg * 1024, ma = R_Q + st * 24576 + gg * 3072;
        uint4* u = v + 2 * i;
        if (i == 0 || i == 8) wg_fence();
        wg_n56_t(hv, u[0].x, u[0].y, u[0].z, u[0].w, db + ma / 16, i > 0);
        wg_n56_t(hv, u[1].x, u[1].y, u[1].z, u[1].w, db + mo / 16 + ((uint64_t)((ma + 1024 - mo) / 16) << 32), 1);
        if (i == 7) TSB(w, 5);
        if (i == 8) TSB(w, 6);
      }
      TS(w, 20);
      wg_commit();
      mbar_wait(bar(B_WO));
      uint32_t bad = 0, bad2 = 0;
#pragma unroll
      for (int i = 0; i < 32; i += 2) { bad |= v[i].w ^ otag; bad2 |= v[i + 1].x ^ otag; }
      asm volatile("{\n.reg .pred p, r;\nsetp.gt.u32 p, %1, 0xffff;\nbar.red.or.pred r, %2, 128, p;\nselp.u32 %0, 1, 0, r;\n}"
                   : "=r"(redo) : "r"(bad | bad2), "r"(4 + w) : "memory");
      wg_wait0();
      pin<28>(hv);
    } while (redo && ++spins < SPIN_LIMIT);
    TSV(w, 16, spins);
  }
  TS(w, 21);

  uint32_t hk[14], nk[14];
  uint32_t* const sm_u = (uint32_t*)(smem + SMALL);
  float* const sm_f = (float*)(smem + SMALL);
  uint32_t wa[28], wb[16], o_ri, o_ci, o_pp, o_gp, f1w;
  {
#pragma unroll
    for (int j = 0; j < 7; j++) {
      hk[2 * j] = add_bf2(xs[j], pack(hv[4 * j], hv[4 * j + 1]));
      hk[2 * j + 1] = add_bf2(xs[8 + j], pack(hv[4 * j + 2], hv[4 * j + 3]));
    }
    float c[6][4];
#pragma unroll
    for (int i = 0; i < 24; i++) c[i >> 2][i & 3] = 0.f;
#pragma unroll
    for (int j = 0; j < 7; j++) {
      mma1688(c[j & 1], hk[2 * j], hk[2 * j + 1], bw[j]);
      mma1688(c[2 + (j & 1)], hk[2 * j], hk[2 * j + 1], hk[2 * j]);
      mma1688(c[4 + (j & 1)], hk[2 * j], hk[2 * j + 1], hk[2 * j + 1]);
    }
    const float q0 = __shfl_sync(0xffffffffu, bsel ? c[2][1] + c[3][1] : c[2][0] + c[3][0], dsrc);
    const float q1 = __shfl_sync(0xffffffffu, bsel ? c[4][3] + c[5][3] : c[4][2] + c[5][2], dsrc);
    st_ll_if(q == 0, scb + o_so, __float_as_uint(c[0][0] + c[1][0]), __float_as_uint(c[0][1] + c[1][1]), __float_as_uint(q0), epoch);
    st_ll_if(q == 0, scb + o_so + 128, __float_as_uint(c[0][2] + c[1][2]), __float_as_uint(c[0][3] + c[1][3]), __float_as_uint(q1), epoch);
    TSB(w, 7);
#pragma unroll
    for (int j = 0; j < 7; j++) {
      hv[4 * j] = lo_f(hk[2 * j]); hv[4 * j + 1] = hi_f(hk[2 * j]); hv[4 * j + 2] = lo_f(hk[2 * j + 1]); hv[4 * j + 3] = hi_f(hk[2 * j + 1]);
    }
    pin<28>(hv);
    uint4 u[4];
    int spins = 0;
#pragma unroll 1
    do {
#pragma unroll
      for (int i = 0; i < 4; i++) u[i] = ld_ll(scb + o_si + 256 * i);
    } while (__any_sync(0xffffffffu, (((u[0].w ^ epoch) | (u[1].w ^ epoch)) | ((u[2].w ^ epoch) | (u[3].w ^ epoch))) != 0) && ++spins < SPIN_LIMIT);
    TS(w, 22);
    float s1 = (__uint_as_float(u[0].x) + __uint_as_float(u[1].x)) + (__uint_as_float(u[2].x) + __uint_as_float(u[3].x));
    float s3 = (__uint_as_float(u[0].y) + __uint_as_float(u[1].y)) + (__uint_as_float(u[2].y) + __uint_as_float(u[3].y));
    float s2 = (__uint_as_float(u[0].z) + __uint_as_float(u[1].z)) + (__uint_as_float(u[2].z) + __uint_as_float(u[3].z));
    s1 += shfl_x(s1, 1); s2 += shfl_x(s2, 1); s3 += shfl_x(s3, 1);
    const float mu = s1 * (1.f / D_);
    float rs;
    asm("rsqrt.approx.ftz.f32 %0, %1;" : "=f"(rs) : "f"(fmaxf(fmaf(s2, 1.f / D_, -mu * mu), 0.f) + 1e-5f));
    uint32_t k1, k2;
    top2(to_key(rs * fmaf(-mu, wsum, s3), inv_tok), k1, k2);
    if (lane == 0) *(uint2*)(sm_u + 2 * warp) = make_uint2(k1, k2);
    const bool up = q >= 2;
    const float nb = -mu * rs;
    const float rsx = shfl_x(rs, 2), nbx = shfl_x(nb, 2);
    const float rs0 = up ? rsx : rs, rs1 = up ? rs : rsx, nb0 = up ? nbx : nb, nb1 = up ? nb : nbx;
#pragma unroll
    for (int j = 0; j < 7; j++) {
      nk[2 * j] = pack(fmaf(hv[4 * j], rs0, nb0), fmaf(hv[4 * j + 1], rs0, nb0));
      nk[2 * j + 1] = pack(fmaf(hv[4 * j + 2], rs1, nb1), fmaf(hv[4 * j + 3], rs1, nb1));
    }
    pin<14>(nk);
    bar_sync(3, 256);
    top2(((const volatile uint32_t*)sm_u)[lane & 15], k1, k2);
    st_ll_if(tid < 8, scb + o_rp, k1, k2, 0, epoch);
    const uint32_t d1 = key_token(k1) - row0, d2 = key_token(k2) - row0;
    if (min(d1, d2) < 16) {
#pragma unroll
      for (int a = 0; a < 2; a++) {
#pragma unroll
        for (int h = 0; h < 2; h++) {
          const uint32_t* k = (a ? hk : nk) + h;
          const bool on = d1 == r8 + 8 * h || d2 == r8 + 8 * h;
          char* p = scb + o_cp + (d2 == r8 + 8 * h ? 2048 : 0) + 1024 * a;
          st_ll_if(on, p, k[0], k[2], k[4], tag_lo(k[6], tag_hi));
          st_ll_if(on, p + 64, k[8], k[10], k[12], tag_up(k[6], tag_hi));
        }
      }
    }
  }
  TS(w, 23);
  uint32_t rk1, rk2;
  uint4 fa, fb;
  const int tk = (lane >> 1) & 1;
  const int n = 16 * (cta >> 2) + 2 * (cta & 3) + (lane & 1) + 2 * (lane & 4), nc = n % 56;
  {
    if (cta < NFFN) mbar_wait(bar(B_FF));
    {
      const uint32_t kr = (lane & 7) + 8 * (lane >> 4), ch = (lane >> 3) & 1;
      const uint32_t a = sb + R_F + (warp & 1) * 14336 + (112 * (warp >> 1) + kr) * 32 + (ch ^ ((lane >> 2) & 1)) * 16;
#pragma unroll
      for (int i = 0; i < 7; i++) ldsm4t(a + 512 * i, wa + 4 * i);
      const uint32_t b = sb + R_F + 28672 + 2048 * min(warp, 6) + kr * 128 + (ch ^ (lane & 7)) * 16;
#pragma unroll
      for (int i = 0; i < 4; i++) ldsm4t(b ^ (32 * i), wb + 4 * i);
    }
    o_ri = keep(OFF(rec[8 * g + warp][lane >> 1])); o_ci = keep(OFF(crow[0][0][2 * (warp >> 1)][q]));
    o_pp = keep(OFF(part[cta][32 * warp + 8 * q + r8])); o_gp = keep(OFF(part[tid >> 1][2 * cta + (tid & 1)]));
    f1w = keep(sb + SMALL + 4 * (64 + 32 * warp + 16 * (q & 1) + 4 * (r8 >> 1) + (r8 & 1) + (q & 2)));
    TSB(w, 10);
    const uint32_t base = sb + X_SL + (16 * warp + (lane & 7)) * 112 + (lane >> 3) * 16;
    uint32_t k[14];
#pragma unroll
    for (int j = 0; j < 14; j++) k[j] = add_bf2(hk[j], nk[j]);
    stsm4(base, k[0], k[2], k[4], k[6]);
    stsm4(base + 896, k[1], k[3], k[5], k[7]);
    stsm4(base + 48, k[6], k[8], k[10], k[12]);
    stsm4(base + 944, k[7], k[9], k[11], k[13]);
    __syncwarp();
    const uint32_t o_fp = keep(OFF(crow[0][0][n / 56][((nc > 31 || (nc > 23 && (nc & 1))) ? 4 : 0) + ((nc & 7) >> 1)]));
    int spins = 0;
    TSB(w, 8);
    uint4 u;
#pragma unroll 1
    do u = ld_ll(scb + o_ri);
    while (__any_sync(0xffffffffu, u.w != epoch) && ++spins < SPIN_LIMIT);
    const uint32_t key = (lane & 1) ? u.y : u.x;
    top2(key, rk1, rk2);
    const uint32_t c1 = __ffs(__ballot_sync(0xffffffffu, key == rk1)) - 1, c2 = __ffs(__ballot_sync(0xffffffffu, key == rk2)) - 1;
    TS(w, 24);
    if (tid == 0) *(uint2*)(smem + R_WR + 136) = make_uint2(key_token(rk1), key_token(rk2));
    if (cta >= NFFN) { if (lane == 0) mbar_arrive(bar(B_WIN)); }
    else {
      const char* cp = scb + o_ci + (bsel ? c2 : c1) * 2048;
      const char* fp = scb + o_fp + (tk ? c2 : c1) * 2048;
      uint4 t[4];
      uint32_t bad;
#pragma unroll 1
      do {
#pragma unroll
        for (int i = 0; i < 4; i++) t[i] = ld_ll(cp + 64 * i);
        bad = ((t[0].w ^ tag_hi) | (t[1].w ^ tag_hi)) | ((t[2].w ^ tag_hi) | (t[3].w ^ tag_hi));
        if (warp == 7) { fa = ld_ll(fp); fb = ld_ll(fp + 1024); bad |= (fa.w ^ tag_hi) | (fb.w ^ tag_hi); }
        else fa = fb = t[0];
      } while (__any_sync(0xffffffffu, bad > 0xffffu) && ++spins < SPIN_LIMIT);
      if (OUTMODE <= 1 && lane == 0) mbar_arrive(bar(B_WIN));
      const uint32_t kk[14] = {t[0].x, t[0].y, t[0].z, untag(t[0].w, t[1].w), t[1].x, t[1].y, t[1].z,
                               t[2].x, t[2].y, t[2].z, untag(t[2].w, t[3].w), t[3].x, t[3].y, t[3].z};
      float c[4] = {0.f, 0.f, 0.f, 0.f}, d[4] = {0.f, 0.f, 0.f, 0.f};
#pragma unroll
      for (int i = 0; i < 7; i++) mma16816((i & 1) ? d : c, wa[4 * i], wa[4 * i + 1], wa[4 * i + 2], wa[4 * i + 3], kk[2 * i], kk[2 * i + 1]);
      const float z = (q & 2) ? ((q & 1) ? c[3] + d[3] : c[2] + d[2]) : ((q & 1) ? c[1] + d[1] : c[0] + d[0]);
      asm volatile("st.shared.f32 [%0], %1;" ::"r"(f1w), "f"(z) : "memory");
      bar_sync(3, 256);
      TS(w, 25);
      if (warp < 7) {
        const float4* pb = (const float4*)(sm_f + 64 + 16 * bsel + 4 * q);
        float4 gs = pb[0], us = pb[8];
#pragma unroll
        for (int k = 1; k < 4; k++) {
          const float4 a = pb[16 * k], b = pb[16 * k + 8];
          gs.x += a.x; gs.y += a.y; gs.z += a.z; gs.w += a.w; us.x += b.x; us.y += b.y; us.z += b.z; us.w += b.w;
        }
        const uint32_t g0 = pack(gs.x, gs.y), g1 = pack(gs.z, gs.w), u0 = pack(us.x, us.y), u1 = pack(us.z, us.w);
        auto silu = [](float v) { return v * rcp(1.f + ex2(-1.4426950408889634f * v)); };
        const uint32_t b0 = mul_bf2(pack(silu(lo_f(g0)), silu(hi_f(g0))), u0), b1 = mul_bf2(pack(silu(lo_f(g1)), silu(hi_f(g1))), u1);
        float e[4][4];
#pragma unroll
        for (int i = 0; i < 4; i++) {
          e[i][0] = e[i][1] = e[i][2] = e[i][3] = 0.f;
          mma16816(e[i], wb[4 * i], wb[4 * i + 1], wb[4 * i + 2], wb[4 * i + 3], b0, b1);
        }
        float y[4];
#pragma unroll
        for (int i = 0; i < 4; i++) y[i] = (q & 2) ? ((q & 1) ? e[3][i] : e[2][i]) : ((q & 1) ? e[1][i] : e[0][i]);
        st_ll(scb + o_pp, __float_as_uint(y[0]), __float_as_uint(y[1]), __float_as_uint(y[2]), (__float_as_uint(y[3]) & ~15u) | (epoch & 15u));
      }
      TS(w, 26);
      if (OUTMODE == 2 && lane == 0) mbar_arrive(bar(B_WIN));
    }
  }
  const bool gather = warp < 7;
  if (cta >= NFFN) { TSDUMP(); return; }
  float hn_v, h_v, gate;
  __nv_bfloat16* outp;
  if (gather) {
    int spins = 0;
    uint4 pu;
#pragma unroll 1
    do pu = ld_ll(scb + o_gp);
    while (__any_sync(0xffffffffu, ((pu.w ^ epoch) & 15u) != 0) && ++spins < SPIN_LIMIT);
    TSB(w, 9);
    if (OUTMODE == 3 && lane == 0) mbar_arrive(bar(B_WIN));
    const float y0 = __uint_as_float(pu.x), y1 = __uint_as_float(pu.y), y2 = __uint_as_float(pu.z), y3 = __uint_as_float(pu.w & ~15u);
    const bool s1 = lane & 2, s2 = lane & 4;
    const float z0 = (s1 ? y1 : y0) + shfl_x(s1 ? y0 : y1, 2), z2 = (s1 ? y3 : y2) + shfl_x(s1 ? y2 : y3, 2);
    float z = (s2 ? z2 : z0) + shfl_x(s2 ? z0 : z2, 4);
    z += shfl_x(z, 8); z += shfl_x(z, 16);
    if (lane < 8) sm_f[512 + 8 * lane + warp] = z;
    bar_arrive(3, 256);
  } else {
    const uint32_t ua = (nc & 16) ? ((nc & 8) ? fa.w : fa.z) : ((nc & 8) ? fa.y : fa.x);
    const uint32_t ub = (nc & 16) ? ((nc & 8) ? fb.w : fb.z) : ((nc & 8) ? fb.y : fb.x);
    const bool hi = (nc & 1) && (nc >> 3) != 3;
    hn_v = __uint_as_float(keep(hi ? ua & 0xffff0000u : ua << 16)); h_v = __uint_as_float(keep(hi ? ub & 0xffff0000u : ub << 16));
    gate = __uint_as_float(keep(__float_as_uint(rbf(rcp(1.f + ex2(-1.4426950408889634f * rbf(key_score(tk ? rk2 : rk1))))))));
    if (OUTMODE == 3 && lane == 0) mbar_arrive(bar(B_WIN));
    outp = P.out + keep(key_token(tk ? rk2 : rk1) * D_ + n);
    bar_sync(3, 256);
    if (lane < 8) {
      const float4 a = *(const float4*)(sm_f + 512 + 8 * lane), b = *(const float4*)(sm_f + 516 + 8 * lane);
      const float y = ((a.x + a.y) + (a.z + a.w)) + ((b.x + b.y) + b.z);
      *outp = __float2bfloat16_rn(h_v + rbf(hn_v + rbf(rbf(y) * gate)));
      if (cta == 0 && lane == 0) st_relaxed(&sc->epoch[0], epoch);
    }
    if (lane == 0) TSL(0, 27);
    if (lane == 0) TSL(1, 27);
  }
  TSDUMP();
}

typedef CUresult (*EncodeFn)(CUtensorMap*, CUtensorMapDataType, cuuint32_t, void*, const cuuint64_t*, const cuuint64_t*,
                             const cuuint32_t*, const cuuint32_t*, CUtensorMapInterleave, CUtensorMapSwizzle,
                             CUtensorMapL2promotion, CUtensorMapFloatOOBfill);

CUtensorMap make_map(EncodeFn enc, const void* p, int rank, const cuuint64_t* dims, const cuuint64_t* strides,
                     const cuuint32_t* box, CUtensorMapSwizzle sw) {
  CUtensorMap m;
  const cuuint32_t es[5] = {1, 1, 1, 1, 1};
  enc(&m, CU_TENSOR_MAP_DATA_TYPE_BFLOAT16, rank, const_cast<void*>(p), dims, strides, box, es, CU_TENSOR_MAP_INTERLEAVE_NONE, sw,
      CU_TENSOR_MAP_L2_PROMOTION_NONE, CU_TENSOR_MAP_FLOAT_OOB_FILL_NONE);
  return m;
}
CUtensorMap make_map2(EncodeFn enc, const void* p, int cols, int rows, int bc, int br, CUtensorMapSwizzle sw) {
  const cuuint64_t dims[2] = {(cuuint64_t)cols, (cuuint64_t)rows}, strides[1] = {(cuuint64_t)cols * 2};
  const cuuint32_t box[2] = {(cuuint32_t)bc, (cuuint32_t)br};
  return make_map(enc, p, 2, dims, strides, box, sw);
}

}

extern "C" void kernel_launch(void* const* d_in, const int* in_sizes, int n_in, void* d_out, int out_size) {
  (void)in_sizes; (void)n_in; (void)out_size;
  static EncodeFn enc = nullptr;
  static Scratch* sc = nullptr;
  if (!enc) {
    void* fn = nullptr;
    cudaDriverEntryPointQueryResult qr;
    cudaGetDriverEntryPoint("cuTensorMapEncodeTiled", &fn, cudaEnableDefault, &qr);
    enc = (EncodeFn)fn;
    cudaGetSymbolAddress((void**)&sc, g_sc);
    cudaFuncSetAttribute(fused_block_kernel, cudaFuncAttributeMaxDynamicSharedMemorySize, SMEM_BYTES);
  }
  Params P;
  P.x = (const __nv_bfloat16*)d_in[0];  P.wqkv = (const __nv_bfloat16*)d_in[1];  P.wo = (const __nv_bfloat16*)d_in[2]; P.wr = (const __nv_bfloat16*)d_in[4];
  P.wg = (const __nv_bfloat16*)d_in[5]; P.wu = (const __nv_bfloat16*)d_in[6]; P.wd = (const __nv_bfloat16*)d_in[7];
  P.out = (__nv_bfloat16*)d_out; P.sc = sc;
  const CUtensorMap tm_w = make_map2(enc, d_in[1], 3 * D_, D_, 64, 112, CU_TENSOR_MAP_SWIZZLE_128B);
  const cuuint64_t od3[3] = {448, 56, 8}, os3[2] = {896, 56 * 896};
  const cuuint32_t ob3[3] = {64, 24, 8};
  const CUtensorMap tm_wo = make_map(enc, P.wo, 3, od3, os3, ob3, CU_TENSOR_MAP_SWIZZLE_128B);
  const CUtensorMap tm_x = make_map2(enc, P.x, D_, S_, 64, 128, CU_TENSOR_MAP_SWIZZLE_128B);
  const CUtensorMap tm_g = make_map2(enc, P.wg, F_, D_, 16, 224, CU_TENSOR_MAP_SWIZZLE_32B);
  const CUtensorMap tm_u = make_map2(enc, P.wu, F_, D_, 16, 224, CU_TENSOR_MAP_SWIZZLE_32B);
  const cuuint64_t dd3[3] = {64, F_, 7}, ds3[2] = {896, 128};
  const cuuint32_t db3[3] = {64, 16, 7};
  const CUtensorMap tm_d = make_map(enc, P.wd, 3, dd3, ds3, db3, CU_TENSOR_MAP_SWIZZLE_128B);
  fused_block_kernel<<<NCTA, NTHREADS, SMEM_BYTES, cudaStreamPerThread>>>(P, tm_x, tm_w, tm_wo, tm_g, tm_u, tm_d);
}
```

```cpp
#include <cuda_runtime.h>
#include <cuda_bf16.h>
#include <cuda.h>
#include <stdint.h>

#define EXP 0
#define PVL 0
#define DEFER 1
#define CLR 1
#define PFF 1
#define FSPLIT 14
#define WOE 0
#define GAE 0
#define OUTMODE 2
namespace {

constexpr int S_ = 2048, D_ = 448, F_ = 1792;
constexpr int NCTA = 128, NFFN = 112, NTHREADS = 384;
constexpr int SPIN_LIMIT = 1 << 18;

constexpr uint32_t R_K = 0;
constexpr uint32_t R_V = 73728;
__host__ __device__ constexpr uint32_t rem_off(int kv, int hh) { return kv ? R_V + 16384 * hh : (hh ? 16384 : 40960); }
__host__ __device__ constexpr uint32_t own_off(int kv, int hh) { return kv ? (hh ? 0 : 32768) : 57344 + 8192 * hh; }
constexpr uint32_t X_SL = R_V + 32768;
constexpr uint32_t R_Q = 131072;
constexpr uint32_t R_M0 = 8192, R_M1 = X_SL + 16384;
constexpr uint32_t R_F = 188416;
constexpr uint32_t R_BAR = 231424;
constexpr uint32_t R_WR = R_BAR + 416;
constexpr uint32_t SMALL = R_Q + 49152;
constexpr uint32_t SMEM_BYTES = R_BAR + 1024;

__host__ __device__ constexpr uint32_t x_off(int c) { return c == 0 ? 57344 : 114688 + 16384 * c; }
__host__ __device__ constexpr uint32_t sec_off(int p) { return p == 0 ? R_K : (p == 1 ? R_V : R_Q); }
enum { B_X = 0, B_W = 7, B_KL = 19, B_VL = B_KL + 2, B_KR = B_VL + 2, B_VR, B_OS0, B_OS1, B_KF, B_VF, B_ROW, B_S4, B_WO, B_FF, B_XS, B_KD0, B_KD1, B_VD0, B_VD1, B_QD0, B_QD1, B_CN, B_E, B_XC = B_E + 3, B_U0, B_WIN, B_S1, B_S2, B_S3, B_COUNT };
__host__ __device__ constexpr int bar_count(int i) { return i < B_WO ? 1 : (i <= B_XS ? 2 : (i < B_XC ? 4 : (i == B_S3 ? 7 : 8))); }

struct __align__(1024) Scratch {
  uint4 kv[32][8][2][2][256];
  uint4 o[2][32][8][4][2][32];
  uint4 stats[128][8][16];
  uint4 part[NFFN][NFFN][2];
  uint4 crow[256][2][8][8];
  uint4 rec[8][128];
  uint32_t epoch[8];
};
__device__ Scratch g_sc;

struct Params {
  const __nv_bfloat16* x; const __nv_bfloat16* wqkv; const __nv_bfloat16* wo; const __nv_bfloat16* wr;
  const __nv_bfloat16* wg; const __nv_bfloat16* wu; const __nv_bfloat16* wd;
  __nv_bfloat16* out; Scratch* sc;
};

__device__ __forceinline__ void wg_n56_t(float* d, uint32_t a0, uint32_t a1, uint32_t a2, uint32_t a3, uint64_t db, int scale_d) {
  asm volatile("{\n.reg .pred p;\nsetp.ne.b32 p, %33, 0;\n"
    "wgmma.mma_async.sync.aligned.m64n56k16.f32.bf16.bf16 "
    "{%0,%1,%2,%3,%4,%5,%6,%7,%8,%9,%10,%11,%12,%13,%14,%15,%16,%17,%18,%19,%20,%21,%22,%23,%24,%25,%26,%27"
    "}, {%28,%29,%30,%31}, %32, p, 1, 1, 1;\n}\n"
    : "+f"(d[0]), "+f"(d[1]), "+f"(d[2]), "+f"(d[3]), "+f"(d[4]), "+f"(d[5]), "+f"(d[6]), "+f"(d[7]),
      "+f"(d[8]), "+f"(d[9]), "+f"(d[10]), "+f"(d[11]), "+f"(d[12]), "+f"(d[13]), "+f"(d[14]), "+f"(d[15]),
      "+f"(d[16]), "+f"(d[17]), "+f"(d[18]), "+f"(d[19]), "+f"(d[20]), "+f"(d[21]), "+f"(d[22]), "+f"(d[23]),
      "+f"(d[24]), "+f"(d[25]), "+f"(d[26]), "+f"(d[27])
      : "r"(a0), "r"(a1), "r"(a2), "r"(a3), "l"(db), "r"(scale_d));
}
__device__ __forceinline__ void wg_n32_t(float* d, uint32_t a0, uint32_t a1, uint32_t a2, uint32_t a3, uint64_t db, int scale_d) {
  asm volatile("{\n.reg .pred p;\nsetp.ne.b32 p, %21, 0;\n"
    "wgmma.mma_async.sync.aligned.m64n32k16.f32.bf16.bf16 "
    "{%0,%1,%2,%3,%4,%5,%6,%7,%8,%9,%10,%11,%12,%13,%14,%15"
    "}, {%16,%17,%18,%19}, %20, p, 1, 1, 1;\n}\n"
    : "+f"(d[0]), "+f"(d[1]), "+f"(d[2]), "+f"(d[3]), "+f"(d[4]), "+f"(d[5]), "+f"(d[6]), "+f"(d[7]),
      "+f"(d[8]), "+f"(d[9]), "+f"(d[10]), "+f"(d[11]), "+f"(d[12]), "+f"(d[13]), "+f"(d[14]), "+f"(d[15])
      : "r"(a0), "r"(a1), "r"(a2), "r"(a3), "l"(db), "r"(scale_d));
}
__device__ __forceinline__ void wg_n64(float* d, uint32_t a0, uint32_t a1, uint32_t a2, uint32_t a3, uint64_t db, int scale_d) {
  asm volatile("{\n.reg .pred p;\nsetp.ne.b32 p, %37, 0;\n"
    "wgmma.mma_async.sync.aligned.m64n64k16.f32.bf16.bf16 "
    "{%0,%1,%2,%3,%4,%5,%6,%7,%8,%9,%10,%11,%12,%13,%14,%15,%16,%17,%18,%19,%20,%21,%22,%23,%24,%25,%26,%27,%28,%29,%30,%31"
    "}, {%32,%33,%34,%35}, %36, p, 1, 1, 0;\n}\n"
    : "+f"(d[0]), "+f"(d[1]), "+f"(d[2]), "+f"(d[3]), "+f"(d[4]), "+f"(d[5]), "+f"(d[6]), "+f"(d[7]),
      "+f"(d[8]), "+f"(d[9]), "+f"(d[10]), "+f"(d[11]), "+f"(d[12]), "+f"(d[13]), "+f"(d[14]), "+f"(d[15]),
      "+f"(d[16]), "+f"(d[17]), "+f"(d[18]), "+f"(d[19]), "+f"(d[20]), "+f"(d[21]), "+f"(d[22]), "+f"(d[23]),
      "+f"(d[24]), "+f"(d[25]), "+f"(d[26]), "+f"(d[27]), "+f"(d[28]), "+f"(d[29]), "+f"(d[30]), "+f"(d[31])
      : "r"(a0), "r"(a1), "r"(a2), "r"(a3), "l"(db), "r"(scale_d));
}
__device__ __forceinline__ void wg_n128(float* d, uint32_t a0, uint32_t a1, uint32_t a2, uint32_t a3, uint64_t db, int scale_d) {
  asm volatile("{\n.reg .pred p;\nsetp.ne.b32 p, %69, 0;\n"
    "wgmma.mma_async.sync.aligned.m64n128k16.f32.bf16.bf16 "
    "{%0,%1,%2,%3,%4,%5,%6,%7,%8,%9,%10,%11,%12,%13,%14,%15,%16,%17,%18,%19,%20,%21,%22,%23,%24,%25,%26,%27,%28,%29,%30,%31,"
    "%32,%33,%34,%35,%36,%37,%38,%39,%40,%41,%42,%43,%44,%45,%46,%47,%48,%49,%50,%51,%52,%53,%54,%55,%56,%57,%58,%59,%60,%61,%62,%63"
    "}, {%64,%65,%66,%67}, %68, p, 1, 1, 0;\n}\n"
    : "+f"(d[0]), "+f"(d[1]), "+f"(d[2]), "+f"(d[3]), "+f"(d[4]), "+f"(d[5]), "+f"(d[6]), "+f"(d[7]),
      "+f"(d[8]), "+f"(d[9]), "+f"(d[10]), "+f"(d[11]), "+f"(d[12]), "+f"(d[13]), "+f"(d[14]), "+f"(d[15]),
      "+f"(d[16]), "+f"(d[17]), "+f"(d[18]), "+f"(d[19]), "+f"(d[20]), "+f"(d[21]), "+f"(d[22]), "+f"(d[23]),
      "+f"(d[24]), "+f"(d[25]), "+f"(d[26]), "+f"(d[27]), "+f"(d[28]), "+f"(d[29]), "+f"(d[30]), "+f"(d[31]),
      "+f"(d[32]), "+f"(d[33]), "+f"(d[34]), "+f"(d[35]), "+f"(d[36]), "+f"(d[37]), "+f"(d[38]), "+f"(d[39]),
      "+f"(d[40]), "+f"(d[41]), "+f"(d[42]), "+f"(d[43]), "+f"(d[44]), "+f"(d[45]), "+f"(d[46]), "+f"(d[47]),
      "+f"(d[48]), "+f"(d[49]), "+f"(d[50]), "+f"(d[51]), "+f"(d[52]), "+f"(d[53]), "+f"(d[54]), "+f"(d[55]),
      "+f"(d[56]), "+f"(d[57]), "+f"(d[58]), "+f"(d[59]), "+f"(d[60]), "+f"(d[61]), "+f"(d[62]), "+f"(d[63])
      : "r"(a0), "r"(a1), "r"(a2), "r"(a3), "l"(db), "r"(scale_d));
}

__device__ __forceinline__ void wg_fence() { asm volatile("wgmma.fence.sync.aligned;" ::: "memory"); }
__device__ __forceinline__ void wg_commit() { asm volatile("wgmma.commit_group.sync.aligned;" ::: "memory"); }
__device__ __forceinline__ void wg_wait0() { asm volatile("wgmma.wait_group.sync.aligned 0;" ::: "memory"); }
__device__ __forceinline__ void wg_wait1() { asm volatile("wgmma.wait_group.sync.aligned 1;" ::: "memory"); }
template <int N> __device__ __forceinline__ void pin(float* d) {
#pragma unroll
  for (int i = 0; i < N; i++) asm volatile("" : "+f"(d[i])::"memory");
}
template <int N> __device__ __forceinline__ void pin(uint32_t* d) {
#pragma unroll
  for (int i = 0; i < N; i++) asm volatile("" : "+r"(d[i])::"memory");
}
__device__ __forceinline__ uint64_t mkdesc(uint32_t addr) {
  return (uint64_t)((addr & 0x3FFFF) >> 4) | (1ull << 16) | (64ull << 32) | (1ull << 62);
}
__device__ __forceinline__ uint64_t mkdesc64(uint32_t addr) {
  return (uint64_t)((addr & 0x3FFFF) >> 4) | (1ull << 16) | (32ull << 32) | (2ull << 62);
}
__device__ __forceinline__ void mbar_init(uint32_t a, int c) { asm volatile("mbarrier.init.shared::cta.b64 [%0], %1;" ::"r"(a), "r"(c) : "memory"); }
__device__ __forceinline__ void mbar_expect(uint32_t a, int b) { asm volatile("mbarrier.arrive.expect_tx.shared::cta.b64 _, [%0], %1;" ::"r"(a), "r"(b) : "memory"); }
__device__ __forceinline__ void mbar_arrive(uint32_t a) { asm volatile("mbarrier.arrive.shared::cta.b64 _, [%0];" ::"r"(a) : "memory"); }
__device__ __forceinline__ void mbar_arrive_if(bool on, uint32_t a) {
  asm volatile("{\n.reg .pred p;\nsetp.ne.u32 p, %1, 0;\n@p mbarrier.arrive.shared::cta.b64 _, [%0];\n}" ::"r"(a), "r"((uint32_t)on) : "memory");
}
__device__ __forceinline__ void mbar_wait(uint32_t a, uint32_t parity = 0) {
  asm volatile("{\n.reg .pred p;\n.reg .u32 n;\nmov.u32 n, 0;\n"
               "W_%=:\nmbarrier.try_wait.parity.shared::cta.b64 p, [%0], %1;\n@p bra D_%=;\n"
               "add.u32 n, n, 1;\nsetp.lt.u32 p, n, 1048576;\n@p bra W_%=;\nD_%=:\n}" ::"r"(a), "r"(parity) : "memory");
}
__device__ __forceinline__ bool mbar_test(uint32_t a) {
  uint32_t r;
  asm volatile("{\n.reg .pred p;\nmbarrier.test_wait.parity.shared::cta.b64 p, [%1], 0;\nselp.u32 %0, 1, 0, p;\n}" : "=r"(r) : "r"(a) : "memory");
  return r;
}
__device__ __forceinline__ void mbar_wait_tma(uint32_t a) {
  asm volatile("{\n.reg .pred p;\nW_%=:\nmbarrier.try_wait.parity.shared::cta.b64 p, [%0], 0;\n@!p bra W_%=;\n}" ::"r"(a) : "memory");
}
__device__ __forceinline__ void bar_sync(int id, int n) { asm volatile("bar.sync %0, %1;" ::"r"(id), "r"(n) : "memory"); }
__device__ __forceinline__ void bar_arrive(int id, int n) { asm volatile("bar.arrive %0, %1;" ::"r"(id), "r"(n) : "memory"); }
__device__ __forceinline__ void fence_async_smem() { asm volatile("fence.proxy.async.shared::cta;" ::: "memory"); }
__device__ __forceinline__ bool elect() {
  uint32_t p;
  asm volatile("{\n.reg .pred p;\nelect.sync _|p, 0xffffffff;\nselp.u32 %0, 1, 0, p;\n}" : "=r"(p));
  return p;
}
__device__ __forceinline__ void tma2d(uint32_t dst, const CUtensorMap* m, int c0, int c1, uint32_t bar) {
  asm volatile("cp.async.bulk.tensor.2d.shared::cluster.global.mbarrier::complete_tx::bytes [%0], [%1, {%3, %4}], [%2];"
               ::"r"(dst), "l"(m), "r"(bar), "r"(c0), "r"(c1) : "memory");
}
__device__ __forceinline__ void tma3d(uint32_t dst, const CUtensorMap* m, int c0, int c1, uint32_t bar) {
  asm volatile("cp.async.bulk.tensor.3d.shared::cluster.global.mbarrier::complete_tx::bytes [%0], [%1, {%3, %4, %5}], [%2];"
               ::"r"(dst), "l"(m), "r"(bar), "r"(c0), "r"(c1), "r"(0) : "memory");
}
__device__ __forceinline__ void bulk_load(uint32_t dst, const void* src, int bytes, uint32_t bar) {
  asm volatile("cp.async.bulk.shared::cluster.global.mbarrier::complete_tx::bytes [%0], [%1], %2, [%3];"
               ::"r"(dst), "l"(src), "r"(bytes), "r"(bar) : "memory");
}
__device__ __forceinline__ void bulk_store(void* dst, uint32_t src, int bytes) {
  asm volatile("cp.async.bulk.global.shared::cta.bulk_group [%0], [%1], %2;" ::"l"(dst), "r"(src), "r"(bytes) : "memory");
}
__device__ __forceinline__ uint32_t ld_relaxed(const uint32_t* p) {
  uint32_t v;
  asm volatile("ld.relaxed.gpu.global.u32 %0, [%1];" : "=r"(v) : "l"(p) : "memory");
  return v;
}
__device__ __forceinline__ void st_relaxed(uint32_t* p, uint32_t v) {
  asm volatile("st.relaxed.gpu.global.u32 [%0], %1;" ::"l"(p), "r"(v) : "memory");
}
__device__ __forceinline__ uint4 ld_ll(const void* p) {
  uint4 v;
  asm volatile("{\n.reg .b128 t;\n.reg .b64 lo, hi;\nld.relaxed.gpu.global.b128 t, [%4];\nmov.b128 {lo, hi}, t;\n"
               "mov.b64 {%0,%1}, lo;\nmov.b64 {%2,%3}, hi;\n}" : "=r"(v.x), "=r"(v.y), "=r"(v.z), "=r"(v.w) : "l"(p) : "memory");
  return v;
}
__device__ __forceinline__ uint4 ld_weak(const void* p) {
  uint4 v;
  asm volatile("ld.global.L1::no_allocate.v4.u32 {%0,%1,%2,%3}, [%4];" : "=r"(v.x), "=r"(v.y), "=r"(v.z), "=r"(v.w) : "l"(p) : "memory");
  return v;
}
__device__ __forceinline__ uint4 ld_ll_if(bool on, const void* p) {
  uint4 v;
  asm volatile("{\n.reg .pred p;\nsetp.ne.u32 p, %5, 0;\n@p ld.relaxed.gpu.global.v4.u32 {%0,%1,%2,%3}, [%4];\n}"
               : "=r"(v.x), "=r"(v.y), "=r"(v.z), "=r"(v.w) : "l"(p), "r"((uint32_t)on) : "memory");
  return v;
}
__device__ __forceinline__ void st_ll(void* p, uint32_t x, uint32_t y, uint32_t z, uint32_t w) {
  asm volatile("{\n.reg .b128 t;\n.reg .b64 lo, hi;\nmov.b64 lo, {%0,%1};\nmov.b64 hi, {%2,%3};\nmov.b128 t, {lo, hi};\n"
               "st.relaxed.gpu.global.b128 [%4], t;\n}" ::"r"(x), "r"(y), "r"(z), "r"(w), "l"(p) : "memory");
}
__device__ __forceinline__ void st_ll_if(bool on, void* p, uint32_t x, uint32_t y, uint32_t z, uint32_t w) {
  asm volatile("{\n.reg .pred p;\nsetp.ne.u32 p, %5, 0;\n@p st.relaxed.gpu.global.v4.u32 [%4], {%0,%1,%2,%3};\n}"
               ::"r"(x), "r"(y), "r"(z), "r"(w), "l"(p), "r"((uint32_t)on) : "memory");
}
template <class T> __device__ __forceinline__ void pinp(T*& p) { asm volatile("" : "+l"(p)); }
__device__ __forceinline__ uint32_t sel(bool c, uint32_t a, uint32_t b) {
  uint32_t r;
  asm("{\n.reg .pred p;\nsetp.ne.u32 p, %3, 0;\nselp.b32 %0, %1, %2, p;\n}" : "=r"(r) : "r"(a), "r"(b), "r"((uint32_t)c));
  return r;
}
__device__ __forceinline__ float self(bool c, float a, float b) { return __uint_as_float(sel(c, __float_as_uint(a), __float_as_uint(b))); }
__device__ __forceinline__ float4 lds128(uint32_t a) {
  float4 v;
  asm volatile("ld.shared.v4.f32 {%0,%1,%2,%3}, [%4];" : "=f"(v.x), "=f"(v.y), "=f"(v.z), "=f"(v.w) : "r"(a) : "memory");
  return v;
}
__device__ __forceinline__ uint32_t tag_lo(uint32_t v, uint32_t tag_hi) { return __byte_perm(v, tag_hi, 0x7610); }
__device__ __forceinline__ uint32_t tag_up(uint32_t v, uint32_t tag_hi) { return __byte_perm(v, tag_hi, 0x7632); }
__device__ __forceinline__ uint32_t untag(uint32_t a, uint32_t b) { return __byte_perm(a, b, 0x5410); }
__device__ __forceinline__ void stsm4(uint32_t a, uint32_t r0, uint32_t r1, uint32_t r2, uint32_t r3) {
  asm volatile("stmatrix.sync.aligned.m8n8.x4.shared.b16 [%0], {%1,%2,%3,%4};" ::"r"(a), "r"(r0), "r"(r1), "r"(r2), "r"(r3) : "memory");
}
__device__ __forceinline__ void ldsm4(uint32_t a, uint32_t* r) {
  asm volatile("ldmatrix.sync.aligned.m8n8.x4.shared.b16 {%0,%1,%2,%3}, [%4];" : "=r"(r[0]), "=r"(r[1]), "=r"(r[2]), "=r"(r[3]) : "r"(a) : "memory");
}
__device__ __forceinline__ void ldsm4t(uint32_t a, uint32_t* r) {
  asm volatile("ldmatrix.sync.aligned.m8n8.x4.trans.shared.b16 {%0,%1,%2,%3}, [%4];" : "=r"(r[0]), "=r"(r[1]), "=r"(r[2]), "=r"(r[3]) : "r"(a) : "memory");
}
__device__ __forceinline__ void mma16816(float* c, uint32_t a0, uint32_t a1, uint32_t a2, uint32_t a3, uint32_t b0, uint32_t b1) {
  asm("mma.sync.aligned.m16n8k16.row.col.f32.bf16.bf16.f32 {%0,%1,%2,%3}, {%4,%5,%6,%7}, {%8,%9}, {%0,%1,%2,%3};"
      : "+f"(c[0]), "+f"(c[1]), "+f"(c[2]), "+f"(c[3]) : "r"(a0), "r"(a1), "r"(a2), "r"(a3), "r"(b0), "r"(b1));
}
__device__ __forceinline__ void mma1688(float* c, uint32_t a0, uint32_t a1, uint32_t b0) {
  asm("mma.sync.aligned.m16n8k8.row.col.f32.bf16.bf16.f32 {%0,%1,%2,%3}, {%4,%5}, {%6}, {%0,%1,%2,%3};"
      : "+f"(c[0]), "+f"(c[1]), "+f"(c[2]), "+f"(c[3]) : "r"(a0), "r"(a1), "r"(b0));
}
__device__ __forceinline__ uint32_t pack(float lo, float hi) {
  uint32_t r;
  asm("cvt.rn.bf16x2.f32 %0, %1, %2;" : "=r"(r) : "f"(hi), "f"(lo));
  return r;
}
__device__ __forceinline__ float lo_f(uint32_t v) { return __uint_as_float(v << 16); }
__device__ __forceinline__ float hi_f(uint32_t v) { return __uint_as_float(v & 0xffff0000u); }
__device__ __forceinline__ float rbf(float v) { return hi_f(pack(0.f, v)); }
__device__ __forceinline__ uint32_t sub_bf2(uint32_t a, uint32_t b) {
  uint32_t r;
  asm("sub.rn.bf16x2 %0, %1, %2;" : "=r"(r) : "r"(a), "r"(b));
  return r;
}
__device__ __forceinline__ uint32_t mul_bf2(uint32_t a, uint32_t b) {
  uint32_t r;
  asm("mul.rn.bf16x2 %0, %1, %2;" : "=r"(r) : "r"(a), "r"(b));
  return r;
}
__device__ __forceinline__ uint32_t add_bf2(uint32_t a, uint32_t b) {
  uint32_t r;
  asm("add.rn.bf16x2 %0, %1, %2;" : "=r"(r) : "r"(a), "r"(b));
  return r;
}
__device__ __forceinline__ float ex2(float x) {
  float r;
  asm("ex2.approx.ftz.f32 %0, %1;" : "=f"(r) : "f"(x));
  return r;
}
__device__ __forceinline__ uint32_t shfl_x(uint32_t v, int m) { return __shfl_xor_sync(0xffffffffu, v, m); }
__device__ __forceinline__ float shfl_x(float v, int m) { return __shfl_xor_sync(0xffffffffu, v, m); }
__device__ __forceinline__ float quad_sum(float v) { v += shfl_x(v, 1); return v + shfl_x(v, 2); }
template <int N> __device__ __forceinline__ void acc_max(const float* s, float& m0, float& m1, float& m2, float& m3) {
#pragma unroll
  for (int i = 0; i < N; i += 8) {
    m0 = fmaxf(m0, fmaxf(s[i], s[i + 1])); m1 = fmaxf(m1, fmaxf(s[i + 2], s[i + 3]));
    m2 = fmaxf(m2, fmaxf(s[i + 4], s[i + 5])); m3 = fmaxf(m3, fmaxf(s[i + 6], s[i + 7]));
  }
}
__device__ __forceinline__ float fmin_nan(float a, float b) { float r; asm("min.NaN.f32 %0, %1, %2;" : "=f"(r) : "f"(a), "f"(b)); return r; }
__device__ __forceinline__ float fmax_nan(float a, float b) { float r; asm("max.NaN.f32 %0, %1, %2;" : "=f"(r) : "f"(a), "f"(b)); return r; }
__device__ __forceinline__ float rcp(float x) {
  float r;
  asm("rcp.approx.ftz.f32 %0, %1;" : "=f"(r) : "f"(x));
  return r;
}
__device__ __forceinline__ uint32_t to_key(float f, uint32_t inv_tok2) {
  const uint32_t u = __float_as_uint(f);
  return (f == f ? (u ^ ((uint32_t)((int)u >> 31) | 0x80000000u)) & 0xfffff000u : 0x1000u) | inv_tok2;
}
__device__ __forceinline__ float key_score(uint32_t k) { return __uint_as_float(k ^ ((uint32_t)((int)~k >> 31) | 0x80000000u)); }
__device__ __forceinline__ uint32_t key_token(uint32_t k) { return (~k >> 1) & 2047u; }
__device__ __forceinline__ uint32_t key_cand(uint32_t k) { return (key_token(k) >> 4) * 2 + (k & 1); }
__device__ __forceinline__ void top2(uint32_t key, uint32_t& k1, uint32_t& k2) {
  k1 = __reduce_max_sync(0xffffffffu, key);
  k2 = __reduce_max_sync(0xffffffffu, key == k1 ? 0u : key);
}
__device__ __forceinline__ uint32_t keep(uint32_t v) { return __shfl_sync(0xffffffffu, v, threadIdx.x & 31); }
#define OFF(member) ((uint32_t)((const char*)&((Scratch*)0)->member - (const char*)0))

#define TSC(a, b)
#define TSH(a, b, c)
#define TSA(a, b, c)
#define TSB(a, b)
#define TS(slot, i)
#define TSL(slot, i)
#define TSV(slot, i, v)
#define TSDUMP()

__global__ void __launch_bounds__(NTHREADS, 1)
fused_block_kernel(const Params P, const __grid_constant__ CUtensorMap tm_x, const __grid_constant__ CUtensorMap tm_w,
                   const __grid_constant__ CUtensorMap tm_wo,
                   const __grid_constant__ CUtensorMap tm_d) {
  extern __shared__ __align__(1024) unsigned char smem[];
  const uint32_t sb = (uint32_t)__cvta_generic_to_shared(smem);
  const int tid = threadIdx.x, lane = tid & 31;
  const int warp = __shfl_sync(0xffffffffu, tid >> 5, 0);
  const int cta = blockIdx.x, m = (cta >> 4) * 2 + (cta & 1), g = (cta >> 1) & 7;
  const int col0 = (56 * g) & ~15;
  const int q = lane & 3, r8 = lane >> 2;
  Scratch* const sc = P.sc;
  auto bar = [&](int i) { return sb + R_BAR + 8 * i; };

  if (warp >= 8) {
    asm volatile("setmaxnreg.dec.sync.aligned.u32 40;");
    const int j = warp - 8;
    if (j == 0 && elect()) {
#pragma unroll
      for (int i = B_X; i < B_W; i++) mbar_init(bar(i), 1);
      asm volatile("fence.mbarrier_init.release.cluster;" ::: "memory");
#pragma unroll 1
      for (int c = 0; c < 7; c++) {
        mbar_expect(bar(B_X + c), 16384);
        tma2d(sb + x_off(c), &tm_x, 64 * c, 128 * m, bar(B_X + c));
      }
    }
    if (j == 1 && elect()) {
      asm volatile("prefetch.tensormap [%0];" ::"l"(&tm_x) : "memory");
      asm volatile("prefetch.tensormap [%0];" ::"l"(&tm_w) : "memory");
#pragma unroll
      for (int i = B_W; i < B_COUNT; i++) mbar_init(bar(i), bar_count(i));
      asm volatile("fence.mbarrier_init.release.cluster;" ::: "memory");
    }
    const uint32_t epoch = ld_relaxed(&sc->epoch[0]) + 1;
    bar_sync(0, NTHREADS);
    if (j == 0) {
      if (elect()) {
        auto publish = [&](int kv, int w) {
          bulk_store(&sc->kv[2 * m + w][g][kv][0][0], sb + own_off(kv, 0) + w * 4096, 4096);
          bulk_store(&sc->kv[2 * m + w][g][kv][1][0], sb + own_off(kv, 1) + w * 4096, 4096);
        };
#pragma unroll 1
        for (int c = 0; c < 12; c++) {
          if (c == 8) mbar_wait_tma(bar(B_XC));
          if (c >= 10) {
            mbar_wait_tma(bar(B_KD0 + c - 10));
            publish(0, c - 10);
          }
          mbar_expect(bar(B_W + c), 14336);
          tma2d(sb + sec_off(c >> 2) + 14336 * (c & 3), &tm_w, col0 + (c >= 8 ? 0 : 448 + 448 * (c >> 2)), 112 * (c & 3), bar(B_W + c));
          if (c == 7) TSL(2, 0);
        }
#pragma unroll 1
        for (int w = 0; w < 2; w++) { mbar_wait_tma(bar(B_VD0 + w)); publish(1, w); }
        asm volatile("cp.async.bulk.commit_group;" ::: "memory");
        TSL(2, 10);
        mbar_wait_tma(bar(B_QD0)); mbar_wait_tma(bar(B_QD1));
        if (WOE < 2) mbar_wait(bar(B_VL + 1 - WOE));
        mbar_expect(bar(B_WO), 49152);
        tma3d(sb + R_Q, &tm_wo, col0, 0, bar(B_WO)); tma3d(sb + R_Q + 24576, &tm_wo, col0, 32, bar(B_WO));
        mbar_expect(bar(B_XS), 16384);
        tma2d(sb + X_SL, &tm_x, col0, 128 * m, bar(B_XS));
        if (cta < NFFN) {
          mbar_expect(bar(B_FF), 14336);
          tma3d(sb + R_F + 28672, &tm_d, 0, 16 * cta, bar(B_FF));
        }
        asm volatile("cp.async.bulk.wait_group.read 0;" ::: "memory");
      }
    } else {
      const uint32_t tag = (epoch & 127) << 16;
      if (j == 3) {
        mbar_wait_tma(bar(B_X + 6));
        if (cta < NFFN && lane < 28) {
          const char* wrow = (const char*)P.wqkv + (4 * cta + lane / 7) * 2688 + (lane % 7) * 128;
          asm volatile("prefetch.global.L2 [%0];" ::"l"(wrow + 1792));
          asm volatile("prefetch.global.L2 [%0];" ::"l"(wrow));
          asm volatile("prefetch.global.L2 [%0];" ::"l"((const char*)P.wo + cta * 3584 + lane * 128));
        }
        float ws = 0.f;
#pragma unroll
        for (int i = 0; i < 7; i++) { const uint32_t v = __ldg((const uint32_t*)P.wr + 32 * i + lane); ws += lo_f(v) + hi_f(v); }
        const uint32_t own = __ldg((const uint32_t*)P.wr + 28 * g + min(lane, 27));
#pragma unroll
        for (int i = 1; i < 32; i <<= 1) ws += shfl_x(ws, i);
        ((uint32_t*)(smem + R_WR))[lane] = lane < 28 ? own : __float_as_uint(ws);
        __syncwarp();
        if (lane == 0) mbar_arrive(bar(B_XS));
        mbar_wait(bar(B_KL + 1));
#pragma unroll 1
        for (int i = lane; i < (PFF ? 98 : 0); i += 32) {
          asm volatile("prefetch.global.L2 [%0];" ::"l"((const char*)P.wg + cta * 12544 + i * 128));
          asm volatile("prefetch.global.L2 [%0];" ::"l"((const char*)P.wu + cta * 12544 + i * 128));
          asm volatile("prefetch.global.L2 [%0];" ::"l"((const char*)P.wd + cta * 12544 + i * 128));
        }
      }
      if (j < 3) {
        const int kv = j - 1, first = max(4 - 2 * m, 0), hh = (lane >> 2) & 1;
        const uint4* src = &sc->kv[2 * m - 4 + max(q, first)][g][kv][hh][0];
        const uint32_t d0 = rem_off(kv, 0), d1 = rem_off(kv, 1), toff = lane * 128 + (q ^ 3) * 16;
        if (first) {
          mbar_wait(bar(B_KD1 + 2 * kv));
#pragma unroll 1
          for (int i = 0; i < 2 * first && kv == 0; i++) {
            *(uint32_t*)(smem + d0 + toff + 8 + (i >> 1) * 4096 + (i & 1) * 64) = 0xff80u;
            *(uint32_t*)(smem + d1 + toff + (i >> 1) * 4096 + (i & 1) * 64) = 0xff80u;
          }
          fence_async_smem();
          __syncwarp();
        }
        int spins = 0;
        uint32_t bad, tries = 0, is_free = 0, lb = bar(B_KL + 2 * kv + hh);
#pragma unroll 1
        do {
          if (tries ? lane == 0 : (lane & 27) == 0) mbar_expect(lb, (4 - first) * (tries ? 8192 : 4096));
          uint32_t todo = ((15u << first) & 15u) * 17u;
#pragma unroll 1
          while (todo && ++spins < SPIN_LIMIT) {
            const uint32_t now = todo & is_free & __ballot_sync(0xffffffffu, (ld_relaxed((const uint32_t*)src + 1010 - 2 * hh) ^ tag) <= 0xffffu);
            if ((now >> lane) & 1) bulk_load(sb + (hh ? d1 : d0) + q * 4096, src, 4096, lb);
            todo &= ~now;
            if (!is_free) is_free = mbar_test(bar(B_KD1 + 2 * kv)) ? 255u : 0u;
          }
          if (lane == 0) TSL(2, 4 + 2 * kv);
          if (tries) mbar_wait(lb, (tries - 1) & 1);
          else { mbar_wait(bar(B_KL + 2 * kv)); if (lane == 0) TSL(2, 8 + kv); mbar_wait(bar(B_KL + 2 * kv + 1)); }
          lb = bar(B_KR + kv);
          tries++;
          bad = 0;
#pragma unroll 1
          for (int i = first; i < 4; i++)
            bad |= (*(const volatile uint32_t*)(smem + d0 + toff + 8 + i * 4096) ^ tag) | (*(const volatile uint32_t*)(smem + d1 + toff + i * 4096) ^ tag);
        } while (__any_sync(0xffffffffu, bad > 0xffffu) && ++spins < SPIN_LIMIT);
        if (lane == 0) { ((uint32_t*)(smem + R_WR))[32 + kv] = tries - 1; mbar_arrive(bar(B_KF + kv)); TSL(2, 1 + kv); }
      } else {
        if (GAE < 2) mbar_wait(bar(B_VL + 1 - GAE)); mbar_wait_tma(bar(B_QD0)); mbar_wait_tma(bar(B_QD1));
#pragma unroll 1
        for (int i = 0; i < 32; i++) {
          const int row = (lane >> 3) + 4 * (i & 1), hh = i >> 4;
          const int src = 56 * ((i >> 1) & 7) + ((row & 1) ? 32 * hh + 8 + row : 24 + 4 * hh + (row >> 1));
          asm volatile("cp.async.cg.shared.global [%0], [%1], 16;" ::"r"(sb + (hh ? R_M1 - 8192 : R_M0) + (i >> 1) * 1024 + row * 128 + ((lane ^ row) & 7) * 16),
                       "l"((const char*)P.wo + src * 896 + col0 * 2 + (lane & 7) * 16) : "memory");
        }
        asm volatile("cp.async.wait_all;" ::: "memory");
        fence_async_smem();
        __syncwarp();
        if (lane == 0) mbar_arrive(bar(B_WO));
      }
    }
    __syncwarp();
    if (j >= 2) {
      const int w = j - 2;
      const uint4* src = &sc->o[0][2 * m + w][0][0][0][0];
      const uint32_t tag = (epoch & 127) << 16;
      int spins = 0;
      mbar_wait(bar(B_U0));
#pragma unroll 1
      while (__any_sync(0xffffffffu, (ld_relaxed(&src[64 * min(lane, 23) + 63].x) ^ tag) > 0xffffu) && ++spins < SPIN_LIMIT) {}
      if (elect()) {
        mbar_expect(bar(B_OS0 + w), 24576);
        bulk_load(sb + (w ? 40960 : R_V), src, 16384, bar(B_OS0 + w));
        bulk_load(sb + (w ? 57344 : 32768), src + 1024, 8192, bar(B_OS0 + w));
      }
      if (lane == 0) TSL(2, 12 + w);
    }
    float hn_v = 0.f, h_v = 0.f, gate = 0.f;
    __nv_bfloat16* outp = P.out;
    if (j == 1 && cta < NFFN) {
      mbar_wait(bar(B_VL + 1));
      const uint32_t row = lane >> 1, dst = sb + R_F + row * 32 + ((lane ^ (lane >> 3)) & 1) * 16;
      const size_t off = (size_t)row * 3584 + cta * 32 + (lane & 1) * 16;
#pragma unroll 1
      for (int i = 0; i < 28; i++) {
        if (i == FSPLIT) { mbar_wait(bar(B_OS0)); mbar_wait(bar(B_OS1)); }
        asm volatile("cp.async.cg.shared.global [%0], [%1], 16;" ::"r"(dst + 512 * i), "l"((const char*)P.wg + off + 57344 * i) : "memory");
        asm volatile("cp.async.cg.shared.global [%0], [%1], 16;" ::"r"(dst + 14336 + 512 * i), "l"((const char*)P.wu + off + 57344 * i) : "memory");
      }
      asm volatile("cp.async.wait_all;" ::: "memory");
      __syncwarp();
      if (lane == 0) { mbar_arrive(bar(B_FF)); TSL(2, 3); }
    }
    if (j == 1) {
      const uint32_t tag_hi = epoch << 16;
      const int tk = (lane >> 1) & 1, n = 16 * (cta >> 2) + 2 * (cta & 3) + (lane & 1) + 2 * (lane & 4), nc = n % 56;
      const uint32_t o_fp = keep(OFF(crow[0][0][min(n / 56, 7)][((nc > 31 || (nc > 23 && (nc & 1))) ? 4 : 0) + ((nc & 7) >> 1)]));
      const uint4* rp = &sc->rec[g][lane];
      uint4 u[4];
      int spins = 0;
      mbar_wait(bar(B_S1));
#pragma unroll 1
      do {
#pragma unroll
        for (int i = 0; i < 4; i++) u[i] = ld_ll(rp + 32 * i);
      } while (__any_sync(0xffffffffu, (((u[0].w ^ epoch) | (u[1].w ^ epoch)) | ((u[2].w ^ epoch) | (u[3].w ^ epoch))) != 0) && ++spins < SPIN_LIMIT);
      if (lane == 0) TSL(2, 14);
      const uint32_t rk1 = __reduce_max_sync(0xffffffffu, max(max(u[0].x, u[1].x), max(u[2].x, u[3].x)));
      uint32_t rk2 = 0;
#pragma unroll
      for (int i = 0; i < 4; i++) rk2 = max(rk2, u[i].x == rk1 ? u[i].y : u[i].x);
      rk2 = __reduce_max_sync(0xffffffffu, rk2);
      const uint32_t c1 = key_cand(rk1), c2 = key_cand(rk2);
      const uint32_t o1 = OFF(crow[0][0][0][lane]) + c1 * 2048, o2 = OFF(crow[0][0][0][lane]) + c2 * 2048;
      uint4 t[4], fa, fb;
#pragma unroll 1
      do {
        t[0] = ld_ll((const char*)sc + o1); t[1] = ld_ll((const char*)sc + o1 + 512); t[2] = ld_ll((const char*)sc + o2); t[3] = ld_ll((const char*)sc + o2 + 512);
      } while (__any_sync(0xffffffffu, (((t[0].w ^ tag_hi) | (t[1].w ^ tag_hi)) | ((t[2].w ^ tag_hi) | (t[3].w ^ tag_hi))) > 0xffffu) && ++spins < SPIN_LIMIT);
#pragma unroll
      for (int i = 0; i < 4; i++) *(uint4*)(smem + SMALL + 4096 + 512 * i + 16 * lane) = t[i];
      if (lane == 0) *(uint2*)(smem + R_WR + 136) = make_uint2(key_token(rk1), key_token(rk2));
      __syncwarp();
      if (lane == 0) { mbar_arrive(bar(B_ROW)); TSL(2, 15); }
      const char* fp = (const char*)sc + o_fp + key_cand(tk ? rk2 : rk1) * 2048;
#pragma unroll 1
      do { fa = ld_ll(fp); fb = ld_ll(fp + 1024); }
      while (__any_sync(0xffffffffu, ((fa.w ^ tag_hi) | (fb.w ^ tag_hi)) > 0xffffu) && ++spins < SPIN_LIMIT);
      const uint32_t ua = (nc & 16) ? ((nc & 8) ? fa.w : fa.z) : ((nc & 8) ? fa.y : fa.x);
      const uint32_t ub = (nc & 16) ? ((nc & 8) ? fb.w : fb.z) : ((nc & 8) ? fb.y : fb.x);
      const bool hi = (nc & 1) && (nc >> 3) != 3;
      hn_v = __uint_as_float(keep(hi ? ua & 0xffff0000u : ua << 16)); h_v = __uint_as_float(keep(hi ? ub & 0xffff0000u : ub << 16));
      gate = __uint_as_float(keep(__float_as_uint(rbf(rcp(1.f + ex2(-1.4426950408889634f * rbf(key_score(tk ? rk2 : rk1))))))));
      outp = P.out + keep(key_token(tk ? rk2 : rk1) * D_ + n);
    }
    mbar_wait(bar(B_WIN)); mbar_wait(bar(B_ROW));
    const uint2 win = *(const uint2*)(smem + R_WR + 136);
    char* const op = (char*)P.out + (128 * m + 32 * j) * 896 + 112 * g;
#pragma unroll 1
    for (int i = 0; i < 7; i++) {
      const int id = lane + 32 * i, r = (id * 9363) >> 16;
      const uint4 v = *(const uint4*)(smem + X_SL + 4096 * j + 16 * id + (r >> 4) * 256);
      const uint32_t tok = 128 * m + 32 * j + r;
      if (OUTMODE != 0 && tok != win.x && tok != win.y) *(uint4*)(op + r * 784 + 16 * id) = v;
    }
    if (j == 1) {
      if (cta < NFFN) {
        mbar_wait(bar(B_S3));
        if (lane < 8) {
          const float4 a = lds128(sb + SMALL + 2048 + 32 * lane), b = lds128(sb + SMALL + 2064 + 32 * lane);
          const float y = ((a.x + a.y) + (a.z + a.w)) + ((b.x + b.y) + b.z);
          *outp = __float2bfloat16_rn(h_v + rbf(hn_v + rbf(rbf(y) * gate)));
        }
        if (cta == 0 && lane == 0) st_relaxed(&sc->epoch[0], epoch);
      }
    }
    return;
  }

  asm volatile("setmaxnreg.inc.sync.aligned.u32 232;");
  const int w = warp >> 2, wi = warp & 3;
  const bool bsel = r8 & 1;
  const int tile = 8 * m + warp, row0 = 16 * tile;
  const int dsrc = (lane & 28) | (r8 >> 1);
  const uint32_t frag_off = (16 * warp + (lane & 15)) * 128 + ((lane >> 4) ^ (lane & 7)) * 16;
  const uint32_t kv_frag = sb + (16 * warp + (lane & 15)) * 64 + ((lane >> 4) ^ ((lane >> 1) & 3)) * 16;
  uint32_t A[112];
  const uint32_t epoch = ld_relaxed(&sc->epoch[0]) + 1, tag_hi = epoch << 16;
  float rstd0, rstd1;
  uint32_t mb[2];
  const uint32_t otag = keep((epoch & 127) << 16);
  char* const scb = (char*)sc;
  auto clear_slots = [&]() {
    const uint32_t e = epoch - 1;
    st_ll_if(lane >= 16, &sc->o[(lane >> 3) & 1][2 * m + w][g][wi][1][lane | 24], (e & 127) << 16, 0, 0, 0);
    st_ll_if(q == 0, &sc->stats[tile][g][r8], 0, 0, 0, e);
    st_ll_if(q == 0, &sc->stats[tile][g][r8 + 8], 0, 0, 0, e);
    st_ll_if(lane == 0, &sc->rec[g][tile], 0, 0, 0, e);
    st_ll_if(warp < 7 && cta < NFFN, &sc->part[16 * warp + 4 * q + (r8 >> 1)][cta][r8 & 1], 0, 0, 0, e);
  };
  if (CLR == 0) clear_slots();
  const int dg = 16 * wi + r8 - 2 * q;
  uint32_t mk[9];
#pragma unroll
  for (int i = 0; i < 9; i++) mk[i] = keep(__funnelshift_lc(0xffffffffu, 0u, __viaddmax_s32(16 * dg, 144 - 128 * i, 0)));
  bar_sync(0, NTHREADS);
  TS(w, 0);
  {
    float c0[4] = {0.f, 0.f, 0.f, 0.f}, c1[4] = {0.f, 0.f, 0.f, 0.f}, c2[4] = {0.f, 0.f, 0.f, 0.f}, c3[4] = {0.f, 0.f, 0.f, 0.f}, c4[4] = {0.f, 0.f, 0.f, 0.f};
    const uint32_t xa = sb + frag_off;
#pragma unroll
    for (int L = 0; L < 7; L++) {
      mbar_wait_tma(bar(B_X + L));
      if (L == 0) TS(w, 28);
      if (L == 6) TS(w, 29);
#pragma unroll
      for (int t = 0; t < 4; t++) ldsm4((xa ^ (32 * t)) + x_off(L), A + 16 * L + 4 * t);
#pragma unroll
      for (int t = 0; t < 4; t++) {
        const uint32_t* a = A + 16 * L + 4 * t;
        mma16816(c0, a[0], a[1], a[2], a[3], 0x3f803f80u, 0x3f803f80u);
        mma1688(c1, a[0], a[1], a[0]); mma1688(c2, a[0], a[1], a[1]);
        mma1688(c3, a[2], a[3], a[2]); mma1688(c4, a[2], a[3], a[3]);
      }
    }
    const float mu0 = c0[0] * (1.f / D_), mu1 = c0[2] * (1.f / D_);
    mb[0] = pack(mu0, mu0); mb[1] = pack(mu1, mu1);
    pin<2>(mb);
    __syncwarp();
    if (lane == 0) mbar_arrive(bar(B_XC));
    if (CLR == 1 && w) clear_slots();
    if (DEFER && w) { mbar_wait_tma(bar(B_CN)); mb[0] = keep(mb[0]); mb[1] = keep(mb[1]); }
#pragma unroll
    for (int i = 0; i < 112; i++) A[i] = sub_bf2(A[i], mb[i & 1]);
    const float q0 = __shfl_sync(0xffffffffu, bsel ? c1[1] + c3[1] : c1[0] + c3[0], dsrc);
    const float q1 = __shfl_sync(0xffffffffu, bsel ? c2[3] + c4[3] : c2[2] + c4[2], dsrc);
    rstd0 = rsqrtf(fmaxf(fmaf(q0, 1.f / D_, -mu0 * mu0), 0.f) + 1e-5f);
    rstd1 = rsqrtf(fmaxf(fmaf(q1, 1.f / D_, -mu1 * mu1), 0.f) + 1e-5f);
    if (DEFER && !w) { pin<112>(A); mbar_arrive_if(lane == 0, bar(B_CN) + (keep(A[111]) & 0)); }
    TS(w, 1);
  }

  uint32_t pk[14], t0[2], t1[2];
  {
    float acc[28];
#pragma unroll
    for (int i = 0; i < 28; i++) acc[i] = 0.f;
#pragma unroll 1
    for (int p = 0; p < 3; p++) {
      if (p + w > 0) bar_sync(1 + w, 256);
      const uint64_t db = mkdesc(sb + sec_off(p) + (g & 1) * 16);
      pin<28>(acc);
#pragma unroll
      for (int c = 0; c < 4; c++) {
        mbar_wait_tma(bar(B_W + 4 * p + c));
        pin<28>(A + 28 * c);
        wg_fence();
#pragma unroll
        for (int t = 7 * c; t < 7 * c + 7; t++) wg_n56_t(acc, A[4 * t], A[4 * t + 1], A[4 * t + 2], A[4 * t + 3], db + t * 128, t > 0);
        wg_commit();
      }
      if (p + w < 3) bar_arrive(2 - w, 256);
      TSA(w, 2 + 3 * p, 2);
      wg_wait0();
      pin<28>(acc);
      TSA(w, 3 + 3 * p, 3);
      const float qs = p == 2 ? 0.18898223650461362f * 1.4426950408889634f : 1.f;
      const float f0 = rstd0 * qs, f1 = rstd1 * qs;
      const uint32_t padv = sel(p == 2, 0x3f803f80u, otag | (p * 0x3f80u));
#pragma unroll
      for (int j = 0; j < 7; j++) {
        pk[j] = pack(acc[4 * j] * f0, acc[4 * j + 1] * f0);
        pk[7 + j] = pack(acc[4 * j + 2] * f1, acc[4 * j + 3] * f1);
      }
#pragma unroll
      for (int h = 0; h < 2; h++) { t0[h] = sel(q < 2, pk[7 * h + 3], padv); t1[h] = sel(q < 2, padv, pk[7 * h + 3]); }
      if (p < 2) {
        mbar_wait_tma(bar(p ? B_KD1 : B_XC));
        const uint32_t b0 = kv_frag + own_off(p, 0), b1 = kv_frag + own_off(p, 1);
        stsm4(b0, pk[0], pk[7], pk[1], pk[8]);   stsm4(b0 ^ 32, pk[2], pk[9], t0[0], t0[1]);
        stsm4(b1, pk[4], pk[11], pk[5], pk[12]); stsm4(b1 ^ 32, pk[6], pk[13], t1[0], t1[1]);
        fence_async_smem();
      }
      __syncwarp();
      if (lane == 0) mbar_arrive(bar(B_KD0 + 2 * p + w));
      TSA(w, 4 + 3 * p, 4);
    }
  }
  float hv[28];
  uint32_t xs[16], bw[7], o_so, o_si, o_cp, o_rp, inv_tok, a_ci, o_pp, o_gp, f1w, f1r, a_wa, a_wb, a_st;
  float wsum;
  const int rloc = r8 + 4 * (q & 2);
  {
    const uint4* const ip = (const uint4*)(scb + keep(OFF(o[0][2 * m + w][0][wi][0][lane])));
    uint4* const op = (uint4*)ip + 256 * g;
    {
      uint32_t qa[8] = {pk[0], pk[7], pk[1], pk[8], pk[2], pk[9], t0[0], t0[1]};
      uint32_t qb[8] = {pk[4], pk[11], pk[5], pk[12], pk[6], pk[13], t1[0], t1[1]};
      const uint64_t d0 = mkdesc64(sb), dw = d0 + w * 256;
      if ((CLR == 1 && !w) || CLR == 2) clear_slots();
      TS(w, 11);
      float s[128], sd[32], o[16];
      uint32_t pp[80];
      auto scores_a = [&](const uint32_t* qq, int hh) {
        const uint64_t df = dw + rem_off(0, hh) / 16, dd = dw + own_off(0, hh) / 16;
        mbar_wait(bar(B_KL + hh));
        wg_fence();
        wg_n64(s, qq[0], qq[1], qq[2], qq[3], df, 0);
        wg_n64(s, qq[4], qq[5], qq[6], qq[7], df + 2, 1);
        wg_n64(sd, qq[0], qq[1], qq[2], qq[3], dd, 0);
        wg_n64(sd, qq[4], qq[5], qq[6], qq[7], dd + 2, 1);
        wg_commit();
      };
      auto scores_b = [&](const uint32_t* qq, int hh) {
        const uint64_t d = dw + rem_off(0, hh) / 16 + 256, d3 = d0 + (w ? own_off(0, hh) : rem_off(0, hh) + 12288) / 16;
        wg_fence();
        wg_n128(s + 32, qq[0], qq[1], qq[2], qq[3], d, 0);
        wg_n128(s + 32, qq[4], qq[5], qq[6], qq[7], d + 2, 1);
        wg_n64(s + 96, qq[0], qq[1], qq[2], qq[3], d3, 0);
        wg_n64(s + 96, qq[4], qq[5], qq[6], qq[7], d3 + 2, 1);
        wg_commit();
        wg_wait1();
        pin<32>(s); pin<32>(sd);
#pragma unroll
        for (int i = 0; i < 32; i++) sd[i] = (8 * ((i >> 2) - ((i >> 1) & 1)) + (i & 1) <= dg) ? sd[i] : s[i];
        pin<32>(sd);
      };
      auto softmax_pv = [&](int hh, bool shift, float m0, float m1, bool hand) {
        auto expo = [&](int lo, int hi) {
#pragma unroll
          for (int i = lo; i < hi; i++) {
            const float* sp = i < 16 ? sd : s;
            const float mm = (i & 1) ? m1 : m0;
            pp[i] = shift ? pack(ex2(sp[2 * i] - mm), ex2(sp[2 * i + 1] - mm)) : pack(ex2(sp[2 * i]), ex2(sp[2 * i + 1]));
          }
          pin<16>(pp + hi - 16);
        };
        auto pv = [&](const uint32_t* p, uint64_t d, bool first) {
#pragma unroll
          for (int k = 0; k < 4; k++) wg_n32_t(o, p[4 * k], p[4 * k + 1], p[4 * k + 2], p[4 * k + 3], d + k * 64, !first || k > 0);
        };
        expo(0, 32);
#pragma unroll
        for (int i = 0; i < 16; i++) {
          const uint32_t k = mk[(i >> 1) - (i & 1) + 1];
          pp[64 + i] = pp[i] & k;
          pp[i] &= ~k;
        }
        pin<16>(pp); pin<16>(pp + 64);
        const uint64_t dv = dw + rem_off(1, hh) / 16;
        if (PVL) mbar_wait(bar(B_KL + hh)); else mbar_wait(bar(B_VL + hh));
        mbar_arrive_if(hand && lane == 0, bar(B_E + 2 * hh + w));
        if (PVL == 1) mbar_wait(bar(B_VL + hh));
        if (PVL < 2) {
          wg_fence();
          pv(pp + 64, dw + own_off(1, hh) / 16, true); pv(pp, dv, false);
          wg_commit();
        }
        expo(32, 48);
        if (PVL == 2) mbar_wait(bar(B_VL + hh));
        wg_fence();
        if (PVL == 2) { pv(pp + 64, dw + own_off(1, hh) / 16, true); pv(pp, dv, false); }
        pv(pp + 16, dv + 256, false);
        wg_commit();
        expo(48, 64);
        TSH(w, 14 + 4 * hh, 14);
        wg_fence();
        pv(pp + 32, dv + 512, false); pv(pp + 48, d0 + (w ? own_off(1, hh) : rem_off(1, hh) + 12288) / 16, false);
        wg_commit();
        wg_wait0();
        pin<16>(o);
      };
      auto finish = [&](int hh, bool check, uint32_t reloaded) {
        const int lsrc = (lane & 28) | (2 - 2 * hh);
        const float sum0 = __shfl_sync(0xffffffffu, o[12], lsrc), sum1 = __shfl_sync(0xffffffffu, o[14], lsrc);
        uint32_t unsafe = 0;
        if (check)
          asm volatile("{\n.reg .pred p, r;\nsetp.ge.f32 p, %1, 0f1F800000;\nsetp.le.and.f32 p, %2, 0f5F800000, p;\n"
                       "bar.red.and.pred r, %3, 128, p;\nselp.u32 %0, %4, 1, r;\n}"
                       : "=r"(unsafe) : "f"(fmin_nan(sum0, sum1)), "f"(fmax_nan(sum0, sum1)), "r"(4 + w), "r"(reloaded) : "memory");
        const float l0 = rcp(sum0), l1 = rcp(sum1);
        uint32_t u[8];
#pragma unroll
        for (int j = 0; j < 4; j++) {
          u[j] = pack(o[4 * j] * l0, o[4 * j + 1] * l0);
          u[4 + j] = pack(o[4 * j + 2] * l1, o[4 * j + 3] * l1);
        }
        const int xsrc = (lane & 28) | (2 * hh + (q >> 1));
        const uint32_t x0 = __shfl_sync(0xffffffffu, u[3], xsrc), x1 = __shfl_sync(0xffffffffu, u[7], xsrc), ps = 0x7610 + (q & 1) * 0x22;
        st_ll_if(!unsafe, op + 65536 * hh, u[0], u[4], u[1], tag_lo(u[5], otag));
        st_ll_if(!unsafe, op + 65536 * hh + 32, __byte_perm(x0, otag, ps), __byte_perm(x1, u[5], ps), u[2], u[6]);
        mbar_arrive_if(hh == 0 && !unsafe && lane == 0, bar(B_U0));
        TSH(w, 15 + 4 * hh, 15);
        return __any_sync(0xffffffffu, unsafe);
      };
      int redo_from;
      bool use_max = true;
      pin<8>(qa); pin<8>(qb);
      scores_a(qa, 0); scores_b(qa, 0);
      if (w) mbar_wait_tma(bar(B_E));
      wg_wait0();
      pin<96>(s + 32);
      TSH(w, 13, 13);
      softmax_pv(0, false, 0.f, 0.f, true);
      mbar_wait(bar(B_KF)); mbar_wait(bar(B_VF));
      const uint2 reload = *(const uint2*)(smem + R_WR + 128);
      scores_a(qb, 1);
      const bool bad0 = finish(0, true, reload.x | reload.y);
      scores_b(qb, 1);
      if (bad0) {
        wg_wait0();
        pin<96>(s + 32);
        redo_from = 0;
        use_max = !__any_sync(0xffffffffu, reload.x | reload.y);
      } else {
        mbar_wait_tma(bar(B_E + 1 + w));
        wg_wait0();
        pin<96>(s + 32);
        TSH(w, 17, 13);
        softmax_pv(1, false, 0.f, 0.f, w == 0);
        redo_from = finish(1, true, 0) ? 1 : 2;
      }
      int handed = redo_from;
#pragma unroll 1
      for (int hh = redo_from; hh < 2;) {
        if (hh) {
#pragma unroll
          for (int i = 0; i < 8; i++) qa[i] = qb[i];
        }
        pin<8>(qa);
        scores_a(qa, hh); scores_b(qa, hh);
        wg_wait0();
        pin<96>(s + 32);
        float m0 = 0.f, m1 = 0.f;
        if (use_max) {
          float m2 = fmaxf(sd[4], sd[5]), m3 = fmaxf(sd[6], sd[7]);
          m0 = fmaxf(sd[0], sd[1]); m1 = fmaxf(sd[2], sd[3]);
          acc_max<24>(sd + 8, m0, m1, m2, m3);
          acc_max<96>(s + 32, m0, m1, m2, m3);
          m0 = fmaxf(m0, m2); m1 = fmaxf(m1, m3);
          m0 = fmaxf(m0, shfl_x(m0, 1)); m1 = fmaxf(m1, shfl_x(m1, 1));
          m0 = fmaxf(m0, shfl_x(m0, 2)); m1 = fmaxf(m1, shfl_x(m1, 2));
        }
        softmax_pv(hh, true, m0, m1, hh > handed && w == 0);
        handed = hh;
        if (finish(hh, !use_max, 0)) use_max = true;
        else hh++;
      }
    }
    int spins = 0;
    uint32_t redo;
#pragma unroll 1
    do {
      uint4 v[32];
      TSB(w, 2);
#pragma unroll
      for (int i = 12; i < 16; i++) v[i] = ld_ll(ip + 256 * (i >> 1) + 32 * (i & 1));
      const uint32_t* sp = &sc->o[1][2 * m + w][lane & 7][wi][1][31].x;
      uint32_t sent = ld_relaxed(sp);
      mbar_wait(bar(B_XS));
      {
        const uint32_t xa = sb + X_SL + (16 * warp + (lane & 7)) * 128 + ((((lane >> 3) + (g & 1)) ^ lane) & 7) * 16;
        ldsm4(xa, xs); ldsm4(xa ^ 64, xs + 4); ldsm4(xa + 1024, xs + 8); ldsm4((xa ^ 64) + 1024, xs + 12);
      }
#pragma unroll
      for (int j = 0; j < 7; j++) bw[j] = sel(r8 == 0, 0x3f803f80u, ((const volatile uint32_t*)(smem + R_WR))[4 * j + q]);
      wsum = ((const volatile float*)(smem + R_WR))[28];
      o_so = keep(OFF(stats[tile][g][r8])); o_si = keep(OFF(stats[tile][4 * (q & 1)][rloc]));
      o_cp = keep(OFF(crow[2 * tile][0][g][q])); o_rp = keep(OFF(rec[g][tile]));
      inv_tok = keep(2 * (2047 - row0 - rloc));
      const uint64_t db = mkdesc(__shfl_sync(0xffffffffu, sb + (g & 1) * 16 + (sent & 0), 0));
      if (spins == 0) {
        const uint32_t a0 = sb + (w ? 40960 : R_V) + 1024 * wi + 16 * lane, a1 = sb + (w ? 40960 : 16384) + 1024 * wi + 16 * lane;
        mbar_wait(bar(B_OS0 + w));
#pragma unroll
        for (int i = 0; i < 12; i++) {
          const float4 f = lds128((i < 8 ? a0 : a1) + 4096 * (i >> 1) + 512 * (i & 1));
          v[i] = make_uint4(__float_as_uint(f.x), __float_as_uint(f.y), __float_as_uint(f.z), __float_as_uint(f.w));
        }
      } else {
#pragma unroll
        for (int i = 0; i < 12; i++) v[i] = ld_ll(ip + 256 * (i >> 1) + 32 * (i & 1));
      }
      TSB(w, 3);
#pragma unroll 1
      while (__any_sync(0xffffffffu, (sent ^ otag) > 0xffffu) && ++spins < SPIN_LIMIT) sent = ld_relaxed(sp);
      TS(w, 12);
#pragma unroll
      for (int i = 0; i < 16; i++) v[16 + i] = ld_ll(ip + 65536 + 256 * (i >> 1) + 32 * (i & 1));
      mbar_wait(bar(B_WO));
      TSB(w, 4);
#pragma unroll
      for (int i = 0; i < 16; i++) {
        const int st = i >> 3, gg = i & 7, mo = (st ? R_M1 : R_M0) + gg * 1024, ma = R_Q + st * 24576 + gg * 3072;
        uint4* u = v + 2 * i;
        if (i == 0 || i == 8) wg_fence();
        wg_n56_t(hv, u[0].x, u[0].y, u[0].z, u[0].w, db + ma / 16, i > 0);
        wg_n56_t(hv, u[1].x, u[1].y, u[1].z, u[1].w, db + mo / 16 + ((uint64_t)((ma + 1024 - mo) / 16) << 32), 1);
        if (i == 7) TSB(w, 5);
        if (i == 8) TSB(w, 6);
      }
      TS(w, 20);
      wg_commit();
      mbar_wait(bar(B_WO));
      uint32_t bad = 0, bad2 = 0;
#pragma unroll
      for (int i = 0; i < 32; i += 2) { bad |= v[i].w ^ otag; bad2 |= v[i + 1].x ^ otag; }
      asm volatile("{\n.reg .pred p, r;\nsetp.gt.u32 p, %1, 0xffff;\nbar.red.or.pred r, %2, 128, p;\nselp.u32 %0, 1, 0, r;\n}"
                   : "=r"(redo) : "r"(bad | bad2), "r"(4 + w) : "memory");
      wg_wait0();
      pin<28>(hv);
    } while (redo && ++spins < SPIN_LIMIT);
  }
  TS(w, 21);

  uint32_t hk[14], nk[14];
  float* const sm_f = (float*)(smem + SMALL);
  uint32_t wa[28], wb[16];
  {
#pragma unroll
    for (int j = 0; j < 7; j++) {
      hk[2 * j] = add_bf2(xs[j], pack(hv[4 * j], hv[4 * j + 1]));
      hk[2 * j + 1] = add_bf2(xs[8 + j], pack(hv[4 * j + 2], hv[4 * j + 3]));
    }
    float c[6][4];
#pragma unroll
    for (int i = 0; i < 24; i++) c[i >> 2][i & 3] = 0.f;
#pragma unroll
    for (int j = 0; j < 7; j++) {
      mma1688(c[j & 1], hk[2 * j], hk[2 * j + 1], bw[j]);
      mma1688(c[2 + (j & 1)], hk[2 * j], hk[2 * j + 1], hk[2 * j]);
      mma1688(c[4 + (j & 1)], hk[2 * j], hk[2 * j + 1], hk[2 * j + 1]);
    }
    const float q0 = __shfl_sync(0xffffffffu, bsel ? c[2][1] + c[3][1] : c[2][0] + c[3][0], dsrc);
    const float q1 = __shfl_sync(0xffffffffu, bsel ? c[4][3] + c[5][3] : c[4][2] + c[5][2], dsrc);
    st_ll_if(q == 0, scb + o_so, __float_as_uint(c[0][0] + c[1][0]), __float_as_uint(c[0][1] + c[1][1]), __float_as_uint(q0), epoch);
    st_ll_if(q == 0, scb + o_so + 128, __float_as_uint(c[0][2] + c[1][2]), __float_as_uint(c[0][3] + c[1][3]), __float_as_uint(q1), epoch);
    TSB(w, 7);
    {
      a_ci = keep(sb + SMALL + 4096 + 1024 * bsel + 256 * (warp >> 1) + 16 * q);
      o_pp = keep(OFF(part[16 * warp + 4 * q + (r8 >> 1)][cta][r8 & 1]));
      o_gp = keep(OFF(part[cta][tid >> 1][tid & 1]));
      f1w = keep(sb + SMALL + 4 * (64 + 32 * warp + 16 * (q & 1) + 4 * (r8 >> 1) + (r8 & 1) + (q & 2)));
      f1r = keep(sb + SMALL + 4 * (64 + 16 * bsel + 4 * q));
      const uint32_t kr = (lane & 7) + 8 * (lane >> 4), ch = (lane >> 3) & 1;
      a_wa = keep(sb + R_F + (warp & 1) * 14336 + (112 * (warp >> 1) + kr) * 32 + (ch ^ ((lane >> 2) & 1)) * 16);
      a_wb = keep(sb + R_F + 28672 + 2048 * min(warp, 6) + kr * 128 + (ch ^ (lane & 7)) * 16);
      a_st = keep(sb + X_SL + 2048 * warp + (lane & 7) * 112 + (lane >> 3) * 16);
    }
#pragma unroll
    for (int j = 0; j < 7; j++) {
      hv[4 * j] = lo_f(hk[2 * j]); hv[4 * j + 1] = hi_f(hk[2 * j]); hv[4 * j + 2] = lo_f(hk[2 * j + 1]); hv[4 * j + 3] = hi_f(hk[2 * j + 1]);
    }
    pin<28>(hv);
    uint4 u[4];
    int spins = 0;
#pragma unroll 1
    do {
#pragma unroll
      for (int i = 0; i < 4; i++) u[i] = ld_ll(scb + o_si + 256 * i);
    } while (__any_sync(0xffffffffu, (((u[0].w ^ epoch) | (u[1].w ^ epoch)) | ((u[2].w ^ epoch) | (u[3].w ^ epoch))) != 0) && ++spins < SPIN_LIMIT);
    TS(w, 22);
    float s1 = (__uint_as_float(u[0].x) + __uint_as_float(u[1].x)) + (__uint_as_float(u[2].x) + __uint_as_float(u[3].x));
    float s3 = (__uint_as_float(u[0].y) + __uint_as_float(u[1].y)) + (__uint_as_float(u[2].y) + __uint_as_float(u[3].y));
    float s2 = (__uint_as_float(u[0].z) + __uint_as_float(u[1].z)) + (__uint_as_float(u[2].z) + __uint_as_float(u[3].z));
    s1 += shfl_x(s1, 1); s2 += shfl_x(s2, 1); s3 += shfl_x(s3, 1);
    const float mu = s1 * (1.f / D_);
    float rs;
    asm("rsqrt.approx.ftz.f32 %0, %1;" : "=f"(rs) : "f"(fmaxf(fmaf(s2, 1.f / D_, -mu * mu), 0.f) + 1e-5f));
    uint32_t k1, k2;
    top2(to_key(rs * fmaf(-mu, wsum, s3), inv_tok), k1, k2);
    const bool up = q >= 2;
    const float nb = -mu * rs;
    const float rsx = shfl_x(rs, 2), nbx = shfl_x(nb, 2);
    const float rs0 = up ? rsx : rs, rs1 = up ? rs : rsx, nb0 = up ? nbx : nb, nb1 = up ? nb : nbx;
#pragma unroll
    for (int j = 0; j < 7; j++) {
      nk[2 * j] = pack(fmaf(hv[4 * j], rs0, nb0), fmaf(hv[4 * j + 1], rs0, nb0));
      nk[2 * j + 1] = pack(fmaf(hv[4 * j + 2], rs1, nb1), fmaf(hv[4 * j + 3], rs1, nb1));
    }
    const uint32_t d1 = key_token(k1) & 15, d2 = key_token(k2) & 15;
#pragma unroll
    for (int a = 0; a < 2; a++) {
#pragma unroll
      for (int h = 0; h < 2; h++) {
        const uint32_t* k = (a ? hk : nk) + h;
        const bool on = d1 == r8 + 8 * h || d2 == r8 + 8 * h;
        char* p = scb + o_cp + (d2 == r8 + 8 * h ? 2048 : 0) + 1024 * a;
        st_ll_if(on, p, k[0], k[2], k[4], tag_lo(k[6], tag_hi));
        st_ll_if(on, p + 64, k[8], k[10], k[12], tag_up(k[6], tag_hi));
      }
      if (a == 0) { st_ll_if(lane == 0, scb + o_rp, k1, k2 | 1, 0, epoch); mbar_arrive_if(lane == 0, bar(B_S1)); }
    }
  }
  TS(w, 23);
  {
    if (cta < NFFN) mbar_wait(bar(B_FF));
#pragma unroll
    for (int i = 0; i < 7; i++) ldsm4t(a_wa + 512 * i, wa + 4 * i);
#pragma unroll
    for (int i = 0; i < 4; i++) ldsm4t(a_wb ^ (32 * i), wb + 4 * i);
    const uint32_t base = a_st;
    __syncwarp();
    uint32_t k[14];
#pragma unroll
    for (int j = 0; j < 14; j++) k[j] = add_bf2(hk[j], nk[j]);
    stsm4(base, k[0], k[2], k[4], k[6]);
    stsm4(base + 896, k[1], k[3], k[5], k[7]);
    stsm4(base + 48, k[6], k[8], k[10], k[12]);
    stsm4(base + 944, k[7], k[9], k[11], k[13]);
    __syncwarp();
    if (cta >= NFFN) { if (lane == 0) mbar_arrive(bar(B_WIN)); }
    else {
      TSB(w, 8);
      mbar_wait(bar(B_ROW));
      TS(w, 24);
      uint4 t[4];
#pragma unroll
      for (int i = 0; i < 4; i++) { const float4 f = lds128(a_ci + 64 * i); t[i] = make_uint4(__float_as_uint(f.x), __float_as_uint(f.y), __float_as_uint(f.z), __float_as_uint(f.w)); }
      if (OUTMODE <= 1 && lane == 0) mbar_arrive(bar(B_WIN));
      const uint32_t kk[14] = {t[0].x, t[0].y, t[0].z, untag(t[0].w, t[1].w), t[1].x, t[1].y, t[1].z,
                               t[2].x, t[2].y, t[2].z, untag(t[2].w, t[3].w), t[3].x, t[3].y, t[3].z};
      float c[4] = {0.f, 0.f, 0.f, 0.f}, d[4] = {0.f, 0.f, 0.f, 0.f};
#pragma unroll
      for (int i = 0; i < 7; i++) mma16816((i & 1) ? d : c, wa[4 * i], wa[4 * i + 1], wa[4 * i + 2], wa[4 * i + 3], kk[2 * i], kk[2 * i + 1]);
      const float z = self(q & 2, self(q & 1, c[3], c[2]) + self(q & 1, d[3], d[2]), self(q & 1, c[1], c[0]) + self(q & 1, d[1], d[0]));
      asm volatile("st.shared.f32 [%0], %1;" ::"r"(f1w), "f"(z) : "memory");
      __syncwarp();
      if (lane == 0) mbar_arrive(bar(B_S2));
      if (warp < 7) {
        mbar_wait(bar(B_S2));
        TS(w, 25);
        float4 pa[8];
#pragma unroll
        for (int k = 0; k < 8; k++) pa[k] = lds128(f1r + 128 * k);
        float4 gs = pa[0], us = pa[1];
#pragma unroll
        for (int k = 1; k < 4; k++) {
          const float4 a = pa[2 * k], b = pa[2 * k + 1];
          gs.x += a.x; gs.y += a.y; gs.z += a.z; gs.w += a.w; us.x += b.x; us.y += b.y; us.z += b.z; us.w += b.w;
        }
        const uint32_t g0 = pack(gs.x, gs.y), g1 = pack(gs.z, gs.w), u0 = pack(us.x, us.y), u1 = pack(us.z, us.w);
        auto silu = [](float v) { return v * rcp(1.f + ex2(-1.4426950408889634f * v)); };
        const uint32_t b0 = mul_bf2(pack(silu(lo_f(g0)), silu(hi_f(g0))), u0), b1 = mul_bf2(pack(silu(lo_f(g1)), silu(hi_f(g1))), u1);
        float e[4][4];
#pragma unroll
        for (int i = 0; i < 4; i++) {
          e[i][0] = e[i][1] = e[i][2] = e[i][3] = 0.f;
          mma16816(e[i], wb[4 * i], wb[4 * i + 1], wb[4 * i + 2], wb[4 * i + 3], b0, b1);
        }
        float y[4];
#pragma unroll
        for (int i = 0; i < 4; i++) y[i] = (q & 2) ? ((q & 1) ? e[3][i] : e[2][i]) : ((q & 1) ? e[1][i] : e[0][i]);
        st_ll(scb + o_pp, __float_as_uint(y[0]), __float_as_uint(y[1]), __float_as_uint(y[2]), (__float_as_uint(y[3]) & ~15u) | (epoch & 15u));
      }
      TS(w, 26);
      if (OUTMODE == 2 && lane == 0) mbar_arrive(bar(B_WIN));
    }
  }
  if (cta < NFFN && warp < 7) {
    int spins = 0;
    uint4 pu;
#pragma unroll 1
    do pu = ld_ll(scb + o_gp);
    while (__any_sync(0xffffffffu, ((pu.w ^ epoch) & 15u) != 0) && ++spins < SPIN_LIMIT);
    TSB(w, 9);
    const float y0 = __uint_as_float(pu.x), y1 = __uint_as_float(pu.y), y2 = __uint_as_float(pu.z), y3 = __uint_as_float(pu.w & ~15u);
    const bool s1 = lane & 2, s2 = lane & 4;
    const float z0 = (s1 ? y1 : y0) + shfl_x(s1 ? y0 : y1, 2), z2 = (s1 ? y3 : y2) + shfl_x(s1 ? y2 : y3, 2);
    float z = (s2 ? z2 : z0) + shfl_x(s2 ? z0 : z2, 4);
    z += shfl_x(z, 8); z += shfl_x(z, 16);
    if (lane < 8) sm_f[512 + 8 * lane + warp] = z;
    __syncwarp();
    if (lane == 0) mbar_arrive(bar(B_S3));
  }
  TSDUMP();
}

typedef CUresult (*EncodeFn)(CUtensorMap*, CUtensorMapDataType, cuuint32_t, void*, const cuuint64_t*, const cuuint64_t*,
                             const cuuint32_t*, const cuuint32_t*, CUtensorMapInterleave, CUtensorMapSwizzle,
                             CUtensorMapL2promotion, CUtensorMapFloatOOBfill);

CUtensorMap make_map(EncodeFn enc, const void* p, int rank, const cuuint64_t* dims, const cuuint64_t* strides,
                     const cuuint32_t* box, CUtensorMapSwizzle sw) {
  CUtensorMap m;
  const cuuint32_t es[5] = {1, 1, 1, 1, 1};
  enc(&m, CU_TENSOR_MAP_DATA_TYPE_BFLOAT16, rank, const_cast<void*>(p), dims, strides, box, es, CU_TENSOR_MAP_INTERLEAVE_NONE, sw,
      CU_TENSOR_MAP_L2_PROMOTION_NONE, CU_TENSOR_MAP_FLOAT_OOB_FILL_NONE);
  return m;
}
CUtensorMap make_map2(EncodeFn enc, const void* p, int cols, int rows, int bc, int br, CUtensorMapSwizzle sw) {
  const cuuint64_t dims[2] = {(cuuint64_t)cols, (cuuint64_t)rows}, strides[1] = {(cuuint64_t)cols * 2};
  const cuuint32_t box[2] = {(cuuint32_t)bc, (cuuint32_t)br};
  return make_map(enc, p, 2, dims, strides, box, sw);
}

}

extern "C" void kernel_launch(void* const* d_in, const int* in_sizes, int n_in, void* d_out, int out_size) {
  (void)in_sizes; (void)n_in; (void)out_size;
  static EncodeFn enc = nullptr;
  static Scratch* sc = nullptr;
  if (!enc) {
    void* fn = nullptr;
    cudaDriverEntryPointQueryResult qr;
    cudaGetDriverEntryPoint("cuTensorMapEncodeTiled", &fn, cudaEnableDefault, &qr);
    enc = (EncodeFn)fn;
    cudaGetSymbolAddress((void**)&sc, g_sc);
    cudaFuncSetAttribute(fused_block_kernel, cudaFuncAttributeMaxDynamicSharedMemorySize, SMEM_BYTES);
  }
  Params P;
  P.x = (const __nv_bfloat16*)d_in[0];  P.wqkv = (const __nv_bfloat16*)d_in[1];  P.wo = (const __nv_bfloat16*)d_in[2]; P.wr = (const __nv_bfloat16*)d_in[4];
  P.wg = (const __nv_bfloat16*)d_in[5]; P.wu = (const __nv_bfloat16*)d_in[6]; P.wd = (const __nv_bfloat16*)d_in[7];
  P.out = (__nv_bfloat16*)d_out; P.sc = sc;
  const CUtensorMap tm_w = make_map2(enc, d_in[1], 3 * D_, D_, 64, 112, CU_TENSOR_MAP_SWIZZLE_128B);
  const cuuint64_t od3[3] = {448, 56, 8}, os3[2] = {896, 56 * 896};
  const cuuint32_t ob3[3] = {64, 24, 8};
  const CUtensorMap tm_wo = make_map(enc, P.wo, 3, od3, os3, ob3, CU_TENSOR_MAP_SWIZZLE_128B);
  const CUtensorMap tm_x = make_map2(enc, P.x, D_, S_, 64, 128, CU_TENSOR_MAP_SWIZZLE_128B);
  const cuuint64_t dd3[3] = {64, F_, 7}, ds3[2] = {896, 128};
  const cuuint32_t db3[3] = {64, 16, 7};
  const CUtensorMap tm_d = make_map(enc, P.wd, 3, dd3, ds3, db3, CU_TENSOR_MAP_SWIZZLE_128B);
  fused_block_kernel<<<NCTA, NTHREADS, SMEM_BYTES, cudaStreamPerThread>>>(P, tm_x, tm_w, tm_wo, tm_d);
}
```

```cpp
#include <cuda_runtime.h>
#include <cuda_bf16.h>
#include <cuda.h>
#include <stdint.h>

namespace {

constexpr int S_ = 2048, D_ = 448, F_ = 1792;
constexpr int NCTA = 128, NFFN = 112, NTHREADS = 384;
constexpr int SPIN_LIMIT = 1 << 18;

constexpr uint32_t R_K = 0;
constexpr uint32_t R_V = 73728;
__host__ __device__ constexpr uint32_t rem_off(int kv, int hh) { return kv ? R_V + 16384 * hh : (hh ? 16384 : 40960); }
__host__ __device__ constexpr uint32_t own_off(int kv, int hh) { return kv ? (hh ? 0 : 32768) : 57344 + 8192 * hh; }
constexpr uint32_t X_SL = R_V + 32768;
constexpr uint32_t R_Q = 131072;
constexpr uint32_t R_M0 = 8192, R_M1 = X_SL + 16384;
constexpr uint32_t R_F = 188416;
constexpr uint32_t R_BAR = 231424;
constexpr uint32_t R_WR = R_BAR + 416;
constexpr uint32_t SMALL = R_Q + 49152;
constexpr uint32_t SMEM_BYTES = R_BAR + 1024;

__host__ __device__ constexpr uint32_t x_off(int c) { return c == 0 ? 57344 : 114688 + 16384 * c; }
__host__ __device__ constexpr uint32_t sec_off(int p) { return p == 0 ? R_K : (p == 1 ? R_V : R_Q); }
enum { B_X = 0, B_W = 7, B_KL = 19, B_VL = B_KL + 2, B_KR = B_VL + 2, B_VR, B_OS0, B_OS1, B_ROW, B_FIN, B_WO, B_KVF, B_FF, B_XS, B_KD0, B_KD1, B_VD0, B_VD1, B_QD0, B_QD1, B_CN, B_E, B_XC = B_E + 3, B_U0, B_WIN, B_S1, B_S2, B_COUNT };
__host__ __device__ constexpr int bar_count(int i) { return i < B_WO ? 1 : (i <= B_XS ? 2 : (i < B_XC ? 4 : 8)); }

struct __align__(1024) Scratch {
  uint4 kv[32][8][2][2][256];
  uint4 o[2][32][8][4][2][32];
  uint4 stats[128][8][16];
  uint4 part[NFFN][NFFN][2];
  uint4 crow[256][2][8][8];
  uint4 rec[8][128];
  uint32_t epoch[8];
};
__device__ Scratch g_sc;

struct Params {
  const __nv_bfloat16* x; const __nv_bfloat16* wqkv; const __nv_bfloat16* wo; const __nv_bfloat16* wr;
  const __nv_bfloat16* wg; const __nv_bfloat16* wu; const __nv_bfloat16* wd;
  __nv_bfloat16* out; Scratch* sc;
};

__device__ __forceinline__ void wg_n56_t(float* d, uint32_t a0, uint32_t a1, uint32_t a2, uint32_t a3, uint64_t db, int scale_d) {
  asm volatile("{\n.reg .pred p;\nsetp.ne.b32 p, %33, 0;\n"
    "wgmma.mma_async.sync.aligned.m64n56k16.f32.bf16.bf16 "
    "{%0,%1,%2,%3,%4,%5,%6,%7,%8,%9,%10,%11,%12,%13,%14,%15,%16,%17,%18,%19,%20,%21,%22,%23,%24,%25,%26,%27"
    "}, {%28,%29,%30,%31}, %32, p, 1, 1, 1;\n}\n"
    : "+f"(d[0]), "+f"(d[1]), "+f"(d[2]), "+f"(d[3]), "+f"(d[4]), "+f"(d[5]), "+f"(d[6]), "+f"(d[7]),
      "+f"(d[8]), "+f"(d[9]), "+f"(d[10]), "+f"(d[11]), "+f"(d[12]), "+f"(d[13]), "+f"(d[14]), "+f"(d[15]),
      "+f"(d[16]), "+f"(d[17]), "+f"(d[18]), "+f"(d[19]), "+f"(d[20]), "+f"(d[21]), "+f"(d[22]), "+f"(d[23]),
      "+f"(d[24]), "+f"(d[25]), "+f"(d[26]), "+f"(d[27])
      : "r"(a0), "r"(a1), "r"(a2), "r"(a3), "l"(db), "r"(scale_d));
}
__device__ __forceinline__ void wg_n32_t(float* d, uint32_t a0, uint32_t a1, uint32_t a2, uint32_t a3, uint64_t db, int scale_d) {
  asm volatile("{\n.reg .pred p;\nsetp.ne.b32 p, %21, 0;\n"
    "wgmma.mma_async.sync.aligned.m64n32k16.f32.bf16.bf16 "
    "{%0,%1,%2,%3,%4,%5,%6,%7,%8,%9,%10,%11,%12,%13,%14,%15"
    "}, {%16,%17,%18,%19}, %20, p, 1, 1, 1;\n}\n"
    : "+f"(d[0]), "+f"(d[1]), "+f"(d[2]), "+f"(d[3]), "+f"(d[4]), "+f"(d[5]), "+f"(d[6]), "+f"(d[7]),
      "+f"(d[8]), "+f"(d[9]), "+f"(d[10]), "+f"(d[11]), "+f"(d[12]), "+f"(d[13]), "+f"(d[14]), "+f"(d[15])
      : "r"(a0), "r"(a1), "r"(a2), "r"(a3), "l"(db), "r"(scale_d));
}
__device__ __forceinline__ void wg_n64(float* d, uint32_t a0, uint32_t a1, uint32_t a2, uint32_t a3, uint64_t db, int scale_d) {
  asm volatile("{\n.reg .pred p;\nsetp.ne.b32 p, %37, 0;\n"
    "wgmma.mma_async.sync.aligned.m64n64k16.f32.bf16.bf16 "
    "{%0,%1,%2,%3,%4,%5,%6,%7,%8,%9,%10,%11,%12,%13,%14,%15,%16,%17,%18,%19,%20,%21,%22,%23,%24,%25,%26,%27,%28,%29,%30,%31"
    "}, {%32,%33,%34,%35}, %36, p, 1, 1, 0;\n}\n"
    : "+f"(d[0]), "+f"(d[1]), "+f"(d[2]), "+f"(d[3]), "+f"(d[4]), "+f"(d[5]), "+f"(d[6]), "+f"(d[7]),
      "+f"(d[8]), "+f"(d[9]), "+f"(d[10]), "+f"(d[11]), "+f"(d[12]), "+f"(d[13]), "+f"(d[14]), "+f"(d[15]),
      "+f"(d[16]), "+f"(d[17]), "+f"(d[18]), "+f"(d[19]), "+f"(d[20]), "+f"(d[21]), "+f"(d[22]), "+f"(d[23]),
      "+f"(d[24]), "+f"(d[25]), "+f"(d[26]), "+f"(d[27]), "+f"(d[28]), "+f"(d[29]), "+f"(d[30]), "+f"(d[31])
      : "r"(a0), "r"(a1), "r"(a2), "r"(a3), "l"(db), "r"(scale_d));
}
__device__ __forceinline__ void wg_n128(float* d, uint32_t a0, uint32_t a1, uint32_t a2, uint32_t a3, uint64_t db, int scale_d) {
  asm volatile("{\n.reg .pred p;\nsetp.ne.b32 p, %69, 0;\n"
    "wgmma.mma_async.sync.aligned.m64n128k16.f32.bf16.bf16 "
    "{%0,%1,%2,%3,%4,%5,%6,%7,%8,%9,%10,%11,%12,%13,%14,%15,%16,%17,%18,%19,%20,%21,%22,%23,%24,%25,%26,%27,%28,%29,%30,%31,"
    "%32,%33,%34,%35,%36,%37,%38,%39,%40,%41,%42,%43,%44,%45,%46,%47,%48,%49,%50,%51,%52,%53,%54,%55,%56,%57,%58,%59,%60,%61,%62,%63"
    "}, {%64,%65,%66,%67}, %68, p, 1, 1, 0;\n}\n"
    : "+f"(d[0]), "+f"(d[1]), "+f"(d[2]), "+f"(d[3]), "+f"(d[4]), "+f"(d[5]), "+f"(d[6]), "+f"(d[7]),
      "+f"(d[8]), "+f"(d[9]), "+f"(d[10]), "+f"(d[11]), "+f"(d[12]), "+f"(d[13]), "+f"(d[14]), "+f"(d[15]),
      "+f"(d[16]), "+f"(d[17]), "+f"(d[18]), "+f"(d[19]), "+f"(d[20]), "+f"(d[21]), "+f"(d[22]), "+f"(d[23]),
      "+f"(d[24]), "+f"(d[25]), "+f"(d[26]), "+f"(d[27]), "+f"(d[28]), "+f"(d[29]), "+f"(d[30]), "+f"(d[31]),
      "+f"(d[32]), "+f"(d[33]), "+f"(d[34]), "+f"(d[35]), "+f"(d[36]), "+f"(d[37]), "+f"(d[38]), "+f"(d[39]),
      "+f"(d[40]), "+f"(d[41]), "+f"(d[42]), "+f"(d[43]), "+f"(d[44]), "+f"(d[45]), "+f"(d[46]), "+f"(d[47]),
      "+f"(d[48]), "+f"(d[49]), "+f"(d[50]), "+f"(d[51]), "+f"(d[52]), "+f"(d[53]), "+f"(d[54]), "+f"(d[55]),
      "+f"(d[56]), "+f"(d[57]), "+f"(d[58]), "+f"(d[59]), "+f"(d[60]), "+f"(d[61]), "+f"(d[62]), "+f"(d[63])
      : "r"(a0), "r"(a1), "r"(a2), "r"(a3), "l"(db), "r"(scale_d));
}

__device__ __forceinline__ void wg_fence() { asm volatile("wgmma.fence.sync.aligned;" ::: "memory"); }
__device__ __forceinline__ void wg_commit() { asm volatile("wgmma.commit_group.sync.aligned;" ::: "memory"); }
__device__ __forceinline__ void wg_wait0() { asm volatile("wgmma.wait_group.sync.aligned 0;" ::: "memory"); }
__device__ __forceinline__ void wg_wait1() { asm volatile("wgmma.wait_group.sync.aligned 1;" ::: "memory"); }
template <int N> __device__ __forceinline__ void pin(float* d) {
#pragma unroll
  for (int i = 0; i < N; i++) asm volatile("" : "+f"(d[i])::"memory");
}
template <int N> __device__ __forceinline__ void pin(uint32_t* d) {
#pragma unroll
  for (int i = 0; i < N; i++) asm volatile("" : "+r"(d[i])::"memory");
}
__device__ __forceinline__ uint64_t mkdesc(uint32_t addr) {
  return (uint64_t)((addr & 0x3FFFF) >> 4) | (1ull << 16) | (64ull << 32) | (1ull << 62);
}
__device__ __forceinline__ uint64_t mkdesc64(uint32_t addr) {
  return (uint64_t)((addr & 0x3FFFF) >> 4) | (1ull << 16) | (32ull << 32) | (2ull << 62);
}
__device__ __forceinline__ void mbar_init(uint32_t a, int c) { asm volatile("mbarrier.init.shared::cta.b64 [%0], %1;" ::"r"(a), "r"(c) : "memory"); }
__device__ __forceinline__ void mbar_expect(uint32_t a, int b) { asm volatile("mbarrier.arrive.expect_tx.shared::cta.b64 _, [%0], %1;" ::"r"(a), "r"(b) : "memory"); }
__device__ __forceinline__ void mbar_arrive(uint32_t a) { asm volatile("mbarrier.arrive.shared::cta.b64 _, [%0];" ::"r"(a) : "memory"); }
__device__ __forceinline__ void mbar_arrive_if(bool on, uint32_t a) {
  asm volatile("{\n.reg .pred p;\nsetp.ne.u32 p, %1, 0;\n@p mbarrier.arrive.shared::cta.b64 _, [%0];\n}" ::"r"(a), "r"((uint32_t)on) : "memory");
}
__device__ __forceinline__ void mbar_wait(uint32_t a, uint32_t parity = 0) {
  asm volatile("{\n.reg .pred p;\n.reg .u32 n;\nmov.u32 n, 0;\n"
               "W_%=:\nmbarrier.try_wait.parity.shared::cta.b64 p, [%0], %1;\n@p bra D_%=;\n"
               "add.u32 n, n, 1;\nsetp.lt.u32 p, n, 1048576;\n@p bra W_%=;\nD_%=:\n}" ::"r"(a), "r"(parity) : "memory");
}
__device__ __forceinline__ bool mbar_test(uint32_t a) {
  uint32_t r;
  asm volatile("{\n.reg .pred p;\nmbarrier.test_wait.parity.shared::cta.b64 p, [%1], 0;\nselp.u32 %0, 1, 0, p;\n}" : "=r"(r) : "r"(a) : "memory");
  return r;
}
__device__ __forceinline__ void mbar_wait_tma(uint32_t a) {
  asm volatile("{\n.reg .pred p;\nW_%=:\nmbarrier.try_wait.parity.shared::cta.b64 p, [%0], 0;\n@!p bra W_%=;\n}" ::"r"(a) : "memory");
}
__device__ __forceinline__ void bar_sync(int id, int n) { asm volatile("bar.sync %0, %1;" ::"r"(id), "r"(n) : "memory"); }
__device__ __forceinline__ void bar_arrive(int id, int n) { asm volatile("bar.arrive %0, %1;" ::"r"(id), "r"(n) : "memory"); }
__device__ __forceinline__ void fence_async_smem() { asm volatile("fence.proxy.async.shared::cta;" ::: "memory"); }
__device__ __forceinline__ bool elect() {
  uint32_t p;
  asm volatile("{\n.reg .pred p;\nelect.sync _|p, 0xffffffff;\nselp.u32 %0, 1, 0, p;\n}" : "=r"(p));
  return p;
}
__device__ __forceinline__ void tma2d(uint32_t dst, const CUtensorMap* m, int c0, int c1, uint32_t bar) {
  asm volatile("cp.async.bulk.tensor.2d.shared::cluster.global.mbarrier::complete_tx::bytes [%0], [%1, {%3, %4}], [%2];"
               ::"r"(dst), "l"(m), "r"(bar), "r"(c0), "r"(c1) : "memory");
}
__device__ __forceinline__ void tma3d(uint32_t dst, const CUtensorMap* m, int c0, int c1, uint32_t bar) {
  asm volatile("cp.async.bulk.tensor.3d.shared::cluster.global.mbarrier::complete_tx::bytes [%0], [%1, {%3, %4, %5}], [%2];"
               ::"r"(dst), "l"(m), "r"(bar), "r"(c0), "r"(c1), "r"(0) : "memory");
}
__device__ __forceinline__ void bulk_load(uint32_t dst, const void* src, int bytes, uint32_t bar) {
  asm volatile("cp.async.bulk.shared::cluster.global.mbarrier::complete_tx::bytes [%0], [%1], %2, [%3];"
               ::"r"(dst), "l"(src), "r"(bytes), "r"(bar) : "memory");
}
__device__ __forceinline__ void bulk_store(void* dst, uint32_t src, int bytes) {
  asm volatile("cp.async.bulk.global.shared::cta.bulk_group [%0], [%1], %2;" ::"l"(dst), "r"(src), "r"(bytes) : "memory");
}
__device__ __forceinline__ uint32_t ld_relaxed(const uint32_t* p) {
  uint32_t v;
  asm volatile("ld.relaxed.gpu.global.u32 %0, [%1];" : "=r"(v) : "l"(p) : "memory");
  return v;
}
__device__ __forceinline__ void st_relaxed(uint32_t* p, uint32_t v) {
  asm volatile("st.relaxed.gpu.global.u32 [%0], %1;" ::"l"(p), "r"(v) : "memory");
}
__device__ __forceinline__ uint4 ld_ll(const void* p) {
  uint4 v;
  asm volatile("{\n.reg .b128 t;\n.reg .b64 lo, hi;\nld.relaxed.gpu.global.b128 t, [%4];\nmov.b128 {lo, hi}, t;\n"
               "mov.b64 {%0,%1}, lo;\nmov.b64 {%2,%3}, hi;\n}" : "=r"(v.x), "=r"(v.y), "=r"(v.z), "=r"(v.w) : "l"(p) : "memory");
  return v;
}
__device__ __forceinline__ void st_ll(void* p, uint32_t x, uint32_t y, uint32_t z, uint32_t w) {
  asm volatile("{\n.reg .b128 t;\n.reg .b64 lo, hi;\nmov.b64 lo, {%0,%1};\nmov.b64 hi, {%2,%3};\nmov.b128 t, {lo, hi};\n"
               "st.relaxed.gpu.global.b128 [%4], t;\n}" ::"r"(x), "r"(y), "r"(z), "r"(w), "l"(p) : "memory");
}
__device__ __forceinline__ void st_ll_if(bool on, void* p, uint32_t x, uint32_t y, uint32_t z, uint32_t w) {
  asm volatile("{\n.reg .pred p;\nsetp.ne.u32 p, %5, 0;\n@p st.relaxed.gpu.global.v4.u32 [%4], {%0,%1,%2,%3};\n}"
               ::"r"(x), "r"(y), "r"(z), "r"(w), "l"(p), "r"((uint32_t)on) : "memory");
}
__device__ __forceinline__ uint32_t sel(bool c, uint32_t a, uint32_t b) {
  uint32_t r;
  asm("{\n.reg .pred p;\nsetp.ne.u32 p, %3, 0;\nselp.b32 %0, %1, %2, p;\n}" : "=r"(r) : "r"(a), "r"(b), "r"((uint32_t)c));
  return r;
}
__device__ __forceinline__ float self(bool c, float a, float b) { return __uint_as_float(sel(c, __float_as_uint(a), __float_as_uint(b))); }
__device__ __forceinline__ float4 lds128(uint32_t a) {
  float4 v;
  asm volatile("ld.shared.v4.f32 {%0,%1,%2,%3}, [%4];" : "=f"(v.x), "=f"(v.y), "=f"(v.z), "=f"(v.w) : "r"(a) : "memory");
  return v;
}
template <int I> struct Idx { static constexpr int v = I; };
template <int B, int E, class F> __device__ __forceinline__ void static_for(F f) {
  if constexpr (B < E) { f(Idx<B>()); static_for<B + 1, E>(f); }
}
template <int OFFSET> __device__ __forceinline__ uint4 lds128i(uint32_t a) {
  uint4 v;
  asm volatile("ld.shared.v4.u32 {%0,%1,%2,%3}, [%4+%5];" : "=r"(v.x), "=r"(v.y), "=r"(v.z), "=r"(v.w) : "r"(a), "n"(OFFSET) : "memory");
  return v;
}
__device__ __forceinline__ uint32_t tag_lo(uint32_t v, uint32_t tag_hi) { return __byte_perm(v, tag_hi, 0x7610); }
__device__ __forceinline__ uint32_t tag_up(uint32_t v, uint32_t tag_hi) { return __byte_perm(v, tag_hi, 0x7632); }
__device__ __forceinline__ uint32_t untag(uint32_t a, uint32_t b) { return __byte_perm(a, b, 0x5410); }
__device__ __forceinline__ void stsm4(uint32_t a, uint32_t r0, uint32_t r1, uint32_t r2, uint32_t r3) {
  asm volatile("stmatrix.sync.aligned.m8n8.x4.shared.b16 [%0], {%1,%2,%3,%4};" ::"r"(a), "r"(r0), "r"(r1), "r"(r2), "r"(r3) : "memory");
}
__device__ __forceinline__ void ldsm4(uint32_t a, uint32_t* r) {
  asm volatile("ldmatrix.sync.aligned.m8n8.x4.shared.b16 {%0,%1,%2,%3}, [%4];" : "=r"(r[0]), "=r"(r[1]), "=r"(r[2]), "=r"(r[3]) : "r"(a) : "memory");
}
__device__ __forceinline__ void ldsm4t(uint32_t a, uint32_t* r) {
  asm volatile("ldmatrix.sync.aligned.m8n8.x4.trans.shared.b16 {%0,%1,%2,%3}, [%4];" : "=r"(r[0]), "=r"(r[1]), "=r"(r[2]), "=r"(r[3]) : "r"(a) : "memory");
}
__device__ __forceinline__ void mma16816(float* c, uint32_t a0, uint32_t a1, uint32_t a2, uint32_t a3, uint32_t b0, uint32_t b1) {
  asm("mma.sync.aligned.m16n8k16.row.col.f32.bf16.bf16.f32 {%0,%1,%2,%3}, {%4,%5,%6,%7}, {%8,%9}, {%0,%1,%2,%3};"
      : "+f"(c[0]), "+f"(c[1]), "+f"(c[2]), "+f"(c[3]) : "r"(a0), "r"(a1), "r"(a2), "r"(a3), "r"(b0), "r"(b1));
}
__device__ __forceinline__ void mma1688(float* c, uint32_t a0, uint32_t a1, uint32_t b0) {
  asm("mma.sync.aligned.m16n8k8.row.col.f32.bf16.bf16.f32 {%0,%1,%2,%3}, {%4,%5}, {%6}, {%0,%1,%2,%3};"
      : "+f"(c[0]), "+f"(c[1]), "+f"(c[2]), "+f"(c[3]) : "r"(a0), "r"(a1), "r"(b0));
}
__device__ __forceinline__ uint32_t pack(float lo, float hi) {
  uint32_t r;
  asm("cvt.rn.bf16x2.f32 %0, %1, %2;" : "=r"(r) : "f"(hi), "f"(lo));
  return r;
}
__device__ __forceinline__ float lo_f(uint32_t v) { return __uint_as_float(v << 16); }
__device__ __forceinline__ float hi_f(uint32_t v) { return __uint_as_float(v & 0xffff0000u); }
__device__ __forceinline__ float rbf(float v) { return hi_f(pack(0.f, v)); }
__device__ __forceinline__ uint32_t sub_bf2(uint32_t a, uint32_t b) {
  uint32_t r;
  asm("sub.rn.bf16x2 %0, %1, %2;" : "=r"(r) : "r"(a), "r"(b));
  return r;
}
__device__ __forceinline__ uint32_t mul_bf2(uint32_t a, uint32_t b) {
  uint32_t r;
  asm("mul.rn.bf16x2 %0, %1, %2;" : "=r"(r) : "r"(a), "r"(b));
  return r;
}
__device__ __forceinline__ uint32_t add_bf2(uint32_t a, uint32_t b) {
  uint32_t r;
  asm("add.rn.bf16x2 %0, %1, %2;" : "=r"(r) : "r"(a), "r"(b));
  return r;
}
__device__ __forceinline__ float ex2(float x) {
  float r;
  asm("ex2.approx.ftz.f32 %0, %1;" : "=f"(r) : "f"(x));
  return r;
}
__device__ __forceinline__ float shfl_x(float v, int m) { return __shfl_xor_sync(0xffffffffu, v, m); }
template <int N> __device__ __forceinline__ void acc_max(const float* s, float& m0, float& m1, float& m2, float& m3) {
#pragma unroll
  for (int i = 0; i < N; i += 8) {
    m0 = fmaxf(m0, fmaxf(s[i], s[i + 1])); m1 = fmaxf(m1, fmaxf(s[i + 2], s[i + 3]));
    m2 = fmaxf(m2, fmaxf(s[i + 4], s[i + 5])); m3 = fmaxf(m3, fmaxf(s[i + 6], s[i + 7]));
  }
}
__device__ __forceinline__ float fmin_nan(float a, float b) { float r; asm("min.NaN.f32 %0, %1, %2;" : "=f"(r) : "f"(a), "f"(b)); return r; }
__device__ __forceinline__ float fmax_nan(float a, float b) { float r; asm("max.NaN.f32 %0, %1, %2;" : "=f"(r) : "f"(a), "f"(b)); return r; }
__device__ __forceinline__ float rcp(float x) {
  float r;
  asm("rcp.approx.ftz.f32 %0, %1;" : "=f"(r) : "f"(x));
  return r;
}
__device__ __forceinline__ uint32_t to_key(float f, uint32_t inv_tok2) {
  const uint32_t u = __float_as_uint(f);
  return (f == f ? (u ^ ((uint32_t)((int)u >> 31) | 0x80000000u)) & 0xfffff000u : 0x1000u) | inv_tok2;
}
__device__ __forceinline__ float key_score(uint32_t k) { return __uint_as_float(k ^ ((uint32_t)((int)~k >> 31) | 0x80000000u)); }
__device__ __forceinline__ uint32_t key_token(uint32_t k) { return (~k >> 1) & 2047u; }
__device__ __forceinline__ uint32_t key_cand(uint32_t k) { return (key_token(k) >> 4) * 2 + (k & 1); }
__device__ __forceinline__ void top2(uint32_t key, uint32_t& k1, uint32_t& k2) {
  k1 = __reduce_max_sync(0xffffffffu, key);
  k2 = __reduce_max_sync(0xffffffffu, key == k1 ? 0u : key);
}
__device__ __forceinline__ uint32_t keep(uint32_t v) { return __shfl_sync(0xffffffffu, v, threadIdx.x & 31); }
#define OFF(member) ((uint32_t)((const char*)&((Scratch*)0)->member - (const char*)0))

#define TSC(a, b)
#define TSH(a, b, c)
#define TSA(a, b, c)
#define TSB(a, b)
#define TS(slot, i)
#define TSL(slot, i)
#define TSV(slot, i, v)
#define TSDUMP()

__global__ void __launch_bounds__(NTHREADS, 1)
fused_block_kernel(const Params P, const __grid_constant__ CUtensorMap tm_x, const __grid_constant__ CUtensorMap tm_w,
                   const __grid_constant__ CUtensorMap tm_wo,
                   const __grid_constant__ CUtensorMap tm_d) {
  extern __shared__ __align__(1024) unsigned char smem[];
  const uint32_t sb = (uint32_t)__cvta_generic_to_shared(smem);
  const int tid = threadIdx.x, lane = tid & 31;
  const int warp = __shfl_sync(0xffffffffu, tid >> 5, 0);
  const int cta = blockIdx.x, m = (cta >> 4) * 2 + (cta & 1), g = (cta >> 1) & 7;
  const int col0 = (56 * g) & ~15;
  const int q = lane & 3, r8 = lane >> 2;
  Scratch* const sc = P.sc;
  auto bar = [&](int i) { return sb + R_BAR + 8 * i; };

  if (warp == 0 && elect()) {
#pragma unroll
    for (int i = B_X; i < B_W; i++) mbar_init(bar(i), 1);
    asm volatile("fence.mbarrier_init.release.cluster;" ::: "memory");
#pragma unroll 1
    for (int c = 0; c < 7; c++) {
      mbar_expect(bar(B_X + c), 16384);
      tma2d(sb + x_off(c), &tm_x, 64 * c, 128 * m, bar(B_X + c));
    }
  }
  if (warp >= 8) {
    asm volatile("setmaxnreg.dec.sync.aligned.u32 40;");
    const int j = warp - 8;
    if (j == 1 && elect()) {
      asm volatile("prefetch.tensormap [%0];" ::"l"(&tm_w) : "memory");
#pragma unroll
      for (int i = B_W; i < B_COUNT; i++) mbar_init(bar(i), bar_count(i));
      asm volatile("fence.mbarrier_init.release.cluster;" ::: "memory");
    }
    const uint32_t epoch = ld_relaxed(&sc->epoch[0]) + 1;
    bar_sync(0, NTHREADS);
    if (j == 0) {
      if (elect()) {
        auto publish = [&](int kv, int w) {
          fence_async_smem();
          bulk_store(&sc->kv[2 * m + w][g][kv][0][0], sb + own_off(kv, 0) + w * 4096, 4096);
          bulk_store(&sc->kv[2 * m + w][g][kv][1][0], sb + own_off(kv, 1) + w * 4096, 4096);
        };
#pragma unroll 1
        for (int c = 0; c < 12; c++) {
          if (c == 8) mbar_wait_tma(bar(B_XC));
          if (c >= 10) {
            mbar_wait_tma(bar(B_KD0 + c - 10));
            publish(0, c - 10);
          }
          mbar_expect(bar(B_W + c), 14336);
          tma2d(sb + sec_off(c >> 2) + 14336 * (c & 3), &tm_w, col0 + (c >= 8 ? 0 : 448 + 448 * (c >> 2)), 112 * (c & 3), bar(B_W + c));
          if (c == 7) TSL(2, 0);
        }
#pragma unroll 1
        for (int w = 0; w < 2; w++) { mbar_wait_tma(bar(B_VD0 + w)); publish(1, w); }
        asm volatile("cp.async.bulk.commit_group;" ::: "memory");
        TSL(2, 10);
        mbar_wait_tma(bar(B_QD0)); mbar_wait_tma(bar(B_QD1));
        mbar_wait(bar(B_VL + 1));
        mbar_expect(bar(B_WO), 49152);
        tma3d(sb + R_Q, &tm_wo, col0, 0, bar(B_WO)); tma3d(sb + R_Q + 24576, &tm_wo, col0, 32, bar(B_WO));
        mbar_expect(bar(B_XS), 16384);
        tma2d(sb + X_SL, &tm_x, col0, 128 * m, bar(B_XS));
        if (cta < NFFN) {
          mbar_expect(bar(B_FF), 14336);
          tma3d(sb + R_F + 28672, &tm_d, 0, 16 * cta, bar(B_FF));
        }
        asm volatile("cp.async.bulk.wait_group.read 0;" ::: "memory");
      }
    } else {
      const uint32_t tag = (epoch & 127) << 16;
      if (j == 3) {
        mbar_wait_tma(bar(B_X + 6));
        if (cta < NFFN && lane < 28) {
          const char* wrow = (const char*)P.wqkv + (4 * cta + lane / 7) * 2688 + (lane % 7) * 128;
          asm volatile("prefetch.global.L2 [%0];" ::"l"(wrow + 1792));
          asm volatile("prefetch.global.L2 [%0];" ::"l"(wrow));
          asm volatile("prefetch.global.L2 [%0];" ::"l"((const char*)P.wo + cta * 3584 + lane * 128));
        }
        float ws = 0.f;
#pragma unroll
        for (int i = 0; i < 7; i++) { const uint32_t v = __ldg((const uint32_t*)P.wr + 32 * i + lane); ws += lo_f(v) + hi_f(v); }
        const uint32_t own = __ldg((const uint32_t*)P.wr + 28 * g + min(lane, 27));
#pragma unroll
        for (int i = 1; i < 32; i <<= 1) ws += shfl_x(ws, i);
        ((uint32_t*)(smem + R_WR))[lane] = lane < 28 ? own : __float_as_uint(ws);
        __syncwarp();
        if (lane == 0) mbar_arrive(bar(B_XS));
        mbar_wait(bar(B_KL + 1));
#pragma unroll 1
        for (int i = lane; i < 98; i += 32) {
          asm volatile("prefetch.global.L2 [%0];" ::"l"((const char*)P.wg + cta * 12544 + i * 128));
          asm volatile("prefetch.global.L2 [%0];" ::"l"((const char*)P.wu + cta * 12544 + i * 128));
          asm volatile("prefetch.global.L2 [%0];" ::"l"((const char*)P.wd + cta * 12544 + i * 128));
        }
      }
      if (j < 3) {
        const int kv = j - 1, first = max(4 - 2 * m, 0), hh = (lane >> 2) & 1;
        const uint4* src = &sc->kv[2 * m - 4 + max(q, first)][g][kv][hh][0];
        const uint32_t d0 = rem_off(kv, 0), d1 = rem_off(kv, 1), toff = lane * 128 + (q ^ 3) * 16;
        if (first) {
          mbar_wait(bar(B_KD1 + 2 * kv));
#pragma unroll 1
          for (int i = 0; i < 2 * first && kv == 0; i++) {
            *(uint32_t*)(smem + d0 + toff + 8 + (i >> 1) * 4096 + (i & 1) * 64) = 0xff80u;
            *(uint32_t*)(smem + d1 + toff + (i >> 1) * 4096 + (i & 1) * 64) = 0xff80u;
          }
          fence_async_smem();
          __syncwarp();
        }
        int spins = 0;
        uint32_t bad, tries = 0, is_free = 0, lb = bar(B_KL + 2 * kv + hh);
#pragma unroll 1
        do {
          if (tries ? lane == 0 : (lane & 27) == 0) mbar_expect(lb, (4 - first) * (tries ? 8192 : 4096));
          uint32_t todo = ((15u << first) & 15u) * 17u;
#pragma unroll 1
          while (todo && ++spins < SPIN_LIMIT) {
            const uint32_t now = todo & is_free & __ballot_sync(0xffffffffu, (ld_relaxed((const uint32_t*)src + 1010 - 2 * hh) ^ tag) <= 0xffffu);
            if ((now >> lane) & 1) bulk_load(sb + (hh ? d1 : d0) + q * 4096, src, 4096, lb);
            todo &= ~now;
            if (!is_free) is_free = mbar_test(bar(B_KD1 + 2 * kv)) ? 255u : 0u;
          }
          if (lane == 0) TSL(2, 4 + 2 * kv);
          if (tries) mbar_wait(lb, (tries - 1) & 1);
          else { mbar_wait(bar(B_KL + 2 * kv)); if (lane == 0) TSL(2, 8 + kv); mbar_wait(bar(B_KL + 2 * kv + 1)); }
          lb = bar(B_KR + kv);
          tries++;
          bad = 0;
#pragma unroll 1
          for (int i = 2 * first; i < 8; i++)
            bad |= (*(const volatile uint32_t*)(smem + d0 + toff + 8 + (i >> 1) * 4096 + (i & 1) * 64) ^ tag) |
                   (*(const volatile uint32_t*)(smem + d1 + toff + (i >> 1) * 4096 + (i & 1) * 64) ^ tag);
        } while (__any_sync(0xffffffffu, bad > 0xffffu) && ++spins < SPIN_LIMIT);
        if (lane == 0) { ((uint32_t*)(smem + R_WR))[32 + kv] = tries - 1; mbar_arrive(bar(B_KVF)); TSL(2, 1 + kv); }
      } else {
        mbar_wait(bar(B_VL + 1)); mbar_wait_tma(bar(B_QD0)); mbar_wait_tma(bar(B_QD1));
#pragma unroll 1
        for (int i = 0; i < 32; i++) {
          const int row = (lane >> 3) + 4 * (i & 1), hh = i >> 4;
          const int src = 56 * ((i >> 1) & 7) + ((row & 1) ? 32 * hh + 8 + row : 24 + 4 * hh + (row >> 1));
          asm volatile("cp.async.cg.shared.global [%0], [%1], 16;" ::"r"(sb + (hh ? R_M1 - 8192 : R_M0) + (i >> 1) * 1024 + row * 128 + ((lane ^ row) & 7) * 16),
                       "l"((const char*)P.wo + src * 896 + col0 * 2 + (lane & 7) * 16) : "memory");
        }
        asm volatile("cp.async.wait_all;" ::: "memory");
        fence_async_smem();
        __syncwarp();
        if (lane == 0) mbar_arrive(bar(B_WO));
      }
    }
    __syncwarp();
    if (j >= 2) {
      const int w = j - 2;
      const uint4* src = &sc->o[0][2 * m + w][0][0][0][0];
      const uint32_t tag = (epoch & 127) << 16;
      int spins = 0;
      mbar_wait(bar(B_U0));
#pragma unroll 1
      while (__any_sync(0xffffffffu, (ld_relaxed(&src[64 * min(lane, 23) + 63].x) ^ tag) > 0xffffu) && ++spins < SPIN_LIMIT) {}
      if (elect()) {
        mbar_expect(bar(B_OS0 + w), 24576);
        bulk_load(sb + (w ? 40960 : R_V), src, 16384, bar(B_OS0 + w));
        bulk_load(sb + (w ? 57344 : 32768), src + 1024, 8192, bar(B_OS0 + w));
      }
      if (lane == 0) TSL(2, 12 + w);
    }
    if (j == 1 && cta < NFFN) {
      mbar_wait(bar(B_VL + 1));
      const uint32_t row = lane >> 1, dst = sb + R_F + row * 32 + ((lane ^ (lane >> 3)) & 1) * 16;
      const size_t off = (size_t)row * 3584 + cta * 32 + (lane & 1) * 16;
#pragma unroll 1
      for (int i = 0; i < 28; i++) {
        if (i == 14) { mbar_wait(bar(B_OS0)); mbar_wait(bar(B_OS1)); }
        asm volatile("cp.async.cg.shared.global [%0], [%1], 16;" ::"r"(dst + 512 * i), "l"((const char*)P.wg + off + 57344 * i) : "memory");
        asm volatile("cp.async.cg.shared.global [%0], [%1], 16;" ::"r"(dst + 14336 + 512 * i), "l"((const char*)P.wu + off + 57344 * i) : "memory");
      }
      asm volatile("cp.async.wait_all;" ::: "memory");
      __syncwarp();
      if (lane == 0) { mbar_arrive(bar(B_FF)); TSL(2, 3); }
    }
    if (j == 1) {
      const uint32_t tag_hi = epoch << 16;
      const int tk = (lane >> 1) & 1, n = 16 * (cta >> 2) + 2 * (cta & 3) + (lane & 1) + 2 * (lane & 4), nc = n % 56;
      const uint32_t o_fp = keep(OFF(crow[0][0][min(n / 56, 7)][((nc > 31 || (nc > 23 && (nc & 1))) ? 4 : 0) + ((nc & 7) >> 1)]));
      const uint4* rp = &sc->rec[g][lane];
      uint4 u[4];
      int spins = 0;
      mbar_wait(bar(B_S1));
#pragma unroll 1
      do {
#pragma unroll
        for (int i = 0; i < 4; i++) u[i] = ld_ll(rp + 32 * i);
      } while (__any_sync(0xffffffffu, (((u[0].w ^ epoch) | (u[1].w ^ epoch)) | ((u[2].w ^ epoch) | (u[3].w ^ epoch))) != 0) && ++spins < SPIN_LIMIT);
      if (lane == 0) TSL(2, 14);
      const uint32_t rk1 = __reduce_max_sync(0xffffffffu, max(max(u[0].x, u[1].x), max(u[2].x, u[3].x)));
      uint32_t rk2 = 0;
#pragma unroll
      for (int i = 0; i < 4; i++) rk2 = max(rk2, u[i].x == rk1 ? u[i].y : u[i].x);
      rk2 = __reduce_max_sync(0xffffffffu, rk2);
      const uint32_t c1 = key_cand(rk1), c2 = key_cand(rk2);
      const uint32_t o1 = OFF(crow[0][0][0][lane]) + c1 * 2048, o2 = OFF(crow[0][0][0][lane]) + c2 * 2048;
      uint4 t[4], fa, fb;
#pragma unroll 1
      do {
        t[0] = ld_ll((const char*)sc + o1); t[1] = ld_ll((const char*)sc + o1 + 512); t[2] = ld_ll((const char*)sc + o2); t[3] = ld_ll((const char*)sc + o2 + 512);
      } while (__any_sync(0xffffffffu, (((t[0].w ^ tag_hi) | (t[1].w ^ tag_hi)) | ((t[2].w ^ tag_hi) | (t[3].w ^ tag_hi))) > 0xffffu) && ++spins < SPIN_LIMIT);
#pragma unroll
      for (int i = 0; i < 4; i++) *(uint4*)(smem + SMALL + 4096 + 512 * i + 16 * lane) = t[i];
      if (lane == 0) *(uint2*)(smem + R_WR + 136) = make_uint2(key_token(rk1), key_token(rk2));
      __syncwarp();
      if (lane == 0) { mbar_arrive(bar(B_ROW)); TSL(2, 15); }
      const char* fp = (const char*)sc + o_fp + key_cand(tk ? rk2 : rk1) * 2048;
#pragma unroll 1
      do { fa = ld_ll(fp); fb = ld_ll(fp + 1024); }
      while (__any_sync(0xffffffffu, ((fa.w ^ tag_hi) | (fb.w ^ tag_hi)) > 0xffffu) && ++spins < SPIN_LIMIT);
      const uint32_t ua = (nc & 16) ? ((nc & 8) ? fa.w : fa.z) : ((nc & 8) ? fa.y : fa.x);
      const uint32_t ub = (nc & 16) ? ((nc & 8) ? fb.w : fb.z) : ((nc & 8) ? fb.y : fb.x);
      const bool hi = (nc & 1) && (nc >> 3) != 3;
      if (lane < 8)
        *(uint4*)(smem + SMALL + 2048 + 16 * lane) = make_uint4(hi ? ua & 0xffff0000u : ua << 16, hi ? ub & 0xffff0000u : ub << 16,
            __float_as_uint(rbf(rcp(1.f + ex2(-1.4426950408889634f * rbf(key_score(tk ? rk2 : rk1)))))), key_token(tk ? rk2 : rk1) * D_ + n);
      __syncwarp();
      if (lane == 0) mbar_arrive(bar(B_FIN));
    }
    mbar_wait(bar(B_WIN)); mbar_wait(bar(B_ROW));
    const uint2 win = *(const uint2*)(smem + R_WR + 136);
    char* const op = (char*)P.out + (128 * m + 32 * j) * 896 + 112 * g;
#pragma unroll 1
    for (int i = 0; i < 7; i++) {
      const int id = lane + 32 * i, r = (id * 9363) >> 16;
      const uint4 v = *(const uint4*)(smem + X_SL + 4096 * j + 16 * id + (r >> 4) * 256);
      const uint32_t tok = 128 * m + 32 * j + r;
      if (tok != win.x && tok != win.y) *(uint4*)(op + r * 784 + 16 * id) = v;
    }
    return;
  }

  asm volatile("setmaxnreg.inc.sync.aligned.u32 232;");
  const int w = warp >> 2, wi = warp & 3;
  const bool bsel = r8 & 1;
  const int tile = 8 * m + warp, row0 = 16 * tile;
  const int dsrc = (lane & 28) | (r8 >> 1);
  const uint32_t frag_off = (16 * warp + (lane & 15)) * 128 + ((lane >> 4) ^ (lane & 7)) * 16;
  const uint32_t kv_frag = sb + (16 * warp + (lane & 15)) * 64 + ((lane >> 4) ^ ((lane >> 1) & 3)) * 16;
  uint32_t A[112];
  const uint32_t epoch = ld_relaxed(&sc->epoch[0]) + 1, tag_hi = epoch << 16;
  float rstd0, rstd1;
  uint32_t mb[2];
  const uint32_t otag = keep((epoch & 127) << 16);
  char* const scb = (char*)sc;
  auto clear_slots = [&]() {
    const uint32_t e = epoch - 1;
    const char* po = (const char*)&sc->o[(lane >> 3) & 1][2 * m][g][wi][1][lane | 24];
    const char* ps = (const char*)&sc->stats[8 * m + wi][g][lane & 15];
    const char* pr = (const char*)&sc->rec[g][8 * m + wi];
    const char* pp = (const char*)&sc->part[16 * wi + 4 * q + (r8 >> 1)][cta][r8 & 1];
#pragma unroll
    for (int ww = 0; ww < 2; ww++) {
      st_ll_if(lane >= 16, (void*)(po + 32768 * ww), (e & 127) << 16, 0, 0, 0);
      st_ll_if(lane < 16, (void*)(ps + 8192 * ww), 0, 0, 0, e);
      st_ll_if(lane == 0, (void*)(pr + 64 * ww), 0, 0, 0, e);
      st_ll_if(cta < NFFN && (ww == 0 || wi < 3), (void*)(pp + 229376 * ww), 0, 0, 0, e);
    }
  };
  const int dg = 16 * wi + r8 - 2 * q;
  uint32_t mk[9];
#pragma unroll
  for (int i = 0; i < 9; i++) mk[i] = keep(__funnelshift_lc(0xffffffffu, 0u, __viaddmax_s32(16 * dg, 144 - 128 * i, 0)));
  const int rloc = r8 + 4 * (q & 2);
  bar_sync(0, NTHREADS);
  TS(w, 0);
  {
    float c0[4] = {0.f, 0.f, 0.f, 0.f}, c1[4] = {0.f, 0.f, 0.f, 0.f}, c2[4] = {0.f, 0.f, 0.f, 0.f}, c3[4] = {0.f, 0.f, 0.f, 0.f}, c4[4] = {0.f, 0.f, 0.f, 0.f};
    const uint32_t xa = sb + frag_off;
#pragma unroll
    for (int L = 0; L < 7; L++) {
      mbar_wait_tma(bar(B_X + L));
      if (L == 0) TS(w, 28);
      if (L == 6) TS(w, 29);
#pragma unroll
      for (int t = 0; t < 4; t++) ldsm4((xa ^ (32 * t)) + x_off(L), A + 16 * L + 4 * t);
#pragma unroll
      for (int t = 0; t < 4; t++) {
        const uint32_t* a = A + 16 * L + 4 * t;
        mma16816(c0, a[0], a[1], a[2], a[3], 0x3f803f80u, 0x3f803f80u);
        mma1688(c1, a[0], a[1], a[0]); mma1688(c2, a[0], a[1], a[1]);
        mma1688(c3, a[2], a[3], a[2]); mma1688(c4, a[2], a[3], a[3]);
      }
    }
    const float mu0 = c0[0] * (1.f / D_), mu1 = c0[2] * (1.f / D_);
    mb[0] = pack(mu0, mu0); mb[1] = pack(mu1, mu1);
    pin<2>(mb);
    __syncwarp();
    if (lane == 0) mbar_arrive(bar(B_XC));
    if (w) clear_slots();
    if (w) { mbar_wait_tma(bar(B_CN)); mb[0] = keep(mb[0]); mb[1] = keep(mb[1]); }
#pragma unroll
    for (int i = 0; i < 112; i++) A[i] = sub_bf2(A[i], mb[i & 1]);
    const float q0 = __shfl_sync(0xffffffffu, bsel ? c1[1] + c3[1] : c1[0] + c3[0], dsrc);
    const float q1 = __shfl_sync(0xffffffffu, bsel ? c2[3] + c4[3] : c2[2] + c4[2], dsrc);
    rstd0 = rsqrtf(fmaxf(fmaf(q0, 1.f / D_, -mu0 * mu0), 0.f) + 1e-5f);
    rstd1 = rsqrtf(fmaxf(fmaf(q1, 1.f / D_, -mu1 * mu1), 0.f) + 1e-5f);
    if (!w) { pin<112>(A); mbar_arrive_if(lane == 0, bar(B_CN) + (keep(A[111]) & 0)); }
    TS(w, 1);
  }

  uint32_t pk[14], t0[2], t1[2];
  {
    float acc[28];
#pragma unroll
    for (int i = 0; i < 28; i++) acc[i] = 0.f;
#pragma unroll 1
    for (int p = 0; p < 3; p++) {
      if (p + w > 0) bar_sync(1 + w, 256);
      const uint64_t db = mkdesc(sb + sec_off(p) + (g & 1) * 16);
      pin<28>(acc);
#pragma unroll
      for (int c = 0; c < 4; c++) {
        mbar_wait_tma(bar(B_W + 4 * p + c));
        pin<28>(A + 28 * c);
        wg_fence();
#pragma unroll
        for (int t = 7 * c; t < 7 * c + 7; t++) wg_n56_t(acc, A[4 * t], A[4 * t + 1], A[4 * t + 2], A[4 * t + 3], db + t * 128, t > 0);
        wg_commit();
      }
      if (p + w < 3) bar_arrive(2 - w, 256);
      TSA(w, 2 + 3 * p, 2);
      wg_wait0();
      pin<28>(acc);
      TSA(w, 3 + 3 * p, 3);
      const float qs = p == 2 ? 0.18898223650461362f * 1.4426950408889634f : 1.f;
      const float f0 = rstd0 * qs, f1 = rstd1 * qs;
      const uint32_t padv = sel(p == 2, 0x3f803f80u, otag | (p * 0x3f80u));
#pragma unroll
      for (int j = 0; j < 7; j++) {
        pk[j] = pack(acc[4 * j] * f0, acc[4 * j + 1] * f0);
        pk[7 + j] = pack(acc[4 * j + 2] * f1, acc[4 * j + 3] * f1);
      }
#pragma unroll
      for (int h = 0; h < 2; h++) { t0[h] = sel(q < 2, pk[7 * h + 3], padv); t1[h] = sel(q < 2, padv, pk[7 * h + 3]); }
      if (p < 2) {
        mbar_wait_tma(bar(p ? B_KD1 : B_XC));
        const uint32_t b0 = kv_frag + own_off(p, 0), b1 = kv_frag + own_off(p, 1);
        stsm4(b0, pk[0], pk[7], pk[1], pk[8]);   stsm4(b0 ^ 32, pk[2], pk[9], t0[0], t0[1]);
        stsm4(b1, pk[4], pk[11], pk[5], pk[12]); stsm4(b1 ^ 32, pk[6], pk[13], t1[0], t1[1]);
      } else {
        fence_async_smem();
      }
      __syncwarp();
      if (lane == 0) mbar_arrive(bar(B_KD0 + 2 * p + w));
      TSA(w, 4 + 3 * p, 4);
    }
  }
  float hv[28];
  uint32_t o_so, o_si, o_cp, inv_tok;
  uint32_t xs[16], bw[7], a_ci, o_rp, o_pp, o_gp, f1w, f1r, a_wa, a_wb, a_st;
  float wsum;
  {
    const uint4* const ip = (const uint4*)(scb + keep(OFF(o[0][2 * m + w][0][wi][0][lane])));
    uint4* const op = (uint4*)ip + 256 * g;
    {
      uint32_t qa[8] = {pk[0], pk[7], pk[1], pk[8], pk[2], pk[9], t0[0], t0[1]};
      uint32_t qb[8] = {pk[4], pk[11], pk[5], pk[12], pk[6], pk[13], t1[0], t1[1]};
      const uint64_t d0 = mkdesc64(sb), dw = d0 + w * 256;
      mbar_wait(bar(B_KL));
      TS(w, 11);
      float s[128], sd[32], o[16];
      uint32_t pp[80];
      auto scores_a = [&](const uint32_t* qq, int hh) {
        const uint64_t df = dw + rem_off(0, hh) / 16, dd = dw + own_off(0, hh) / 16;
        wg_fence();
        wg_n64(s, qq[0], qq[1], qq[2], qq[3], df, 0);
        wg_n64(s, qq[4], qq[5], qq[6], qq[7], df + 2, 1);
        wg_n64(sd, qq[0], qq[1], qq[2], qq[3], dd, 0);
        wg_n64(sd, qq[4], qq[5], qq[6], qq[7], dd + 2, 1);
        wg_commit();
      };
      auto scores_b = [&](const uint32_t* qq, int hh) {
        const uint64_t d = dw + rem_off(0, hh) / 16 + 256, d3 = d0 + (w ? own_off(0, hh) : rem_off(0, hh) + 12288) / 16;
        wg_fence();
        wg_n128(s + 32, qq[0], qq[1], qq[2], qq[3], d, 0);
        wg_n128(s + 32, qq[4], qq[5], qq[6], qq[7], d + 2, 1);
        wg_n64(s + 96, qq[0], qq[1], qq[2], qq[3], d3, 0);
        wg_n64(s + 96, qq[4], qq[5], qq[6], qq[7], d3 + 2, 1);
        wg_commit();
        wg_wait1();
        pin<32>(s); pin<32>(sd);
#pragma unroll
        for (int i = 0; i < 32; i++) sd[i] = (8 * ((i >> 2) - ((i >> 1) & 1)) + (i & 1) <= dg) ? sd[i] : s[i];
        pin<32>(sd);
      };
      uint32_t reload = 0;
      auto softmax_pv = [&](int hh, bool shift, float m0, float m1, bool hand) {
        auto expo = [&](int lo, int hi) {
#pragma unroll
          for (int i = lo; i < hi; i++) {
            const float* sp = i < 16 ? sd : s;
            const float mm = (i & 1) ? m1 : m0;
            pp[i] = shift ? pack(ex2(sp[2 * i] - mm), ex2(sp[2 * i + 1] - mm)) : pack(ex2(sp[2 * i]), ex2(sp[2 * i + 1]));
          }
          pin<16>(pp + hi - 16);
        };
        auto pv = [&](const uint32_t* p, uint64_t d, bool first) {
#pragma unroll
          for (int k = 0; k < 4; k++) wg_n32_t(o, p[4 * k], p[4 * k + 1], p[4 * k + 2], p[4 * k + 3], d + k * 64, !first || k > 0);
        };
        expo(0, 32);
#pragma unroll
        for (int i = 0; i < 16; i++) {
          const uint32_t k = mk[(i >> 1) - (i & 1) + 1];
          pp[64 + i] = pp[i] & k;
          pp[i] &= ~k;
        }
        pin<16>(pp); pin<16>(pp + 64);
        const uint64_t dv = dw + rem_off(1, hh) / 16;
        mbar_wait(bar(B_VL));
        mbar_arrive_if(hand && lane == 0, bar(B_E + 2 * hh + w));
        wg_fence();
        pv(pp + 64, dw + own_off(1, hh) / 16, true); pv(pp, dv, false);
        wg_commit();
        expo(32, 48);
        wg_fence();
        pv(pp + 16, dv + 256, false);
        wg_commit();
        expo(48, 64);
        TSH(w, 14 + 4 * hh, 14);
        wg_fence();
        pv(pp + 32, dv + 512, false); pv(pp + 48, d0 + (w ? own_off(1, hh) : rem_off(1, hh) + 12288) / 16, false);
        wg_commit();
        if (!shift && hh == 0) {
          mbar_wait(bar(B_KVF));
          reload = ((const volatile uint32_t*)(smem + R_WR))[32] | ((const volatile uint32_t*)(smem + R_WR))[33];
        }
        wg_wait0();
        pin<16>(o);
      };
      auto finish = [&](int hh, bool check, uint32_t reloaded) {
        const int lsrc = (lane & 28) | (2 - 2 * hh);
        const float sum0 = __shfl_sync(0xffffffffu, o[12], lsrc), sum1 = __shfl_sync(0xffffffffu, o[14], lsrc);
        uint32_t unsafe = 0;
        if (check)
          asm volatile("{\n.reg .pred p, r;\nsetp.ge.f32 p, %1, 0f1F800000;\nsetp.le.and.f32 p, %2, 0f5F800000, p;\n"
                       "bar.red.and.pred r, %3, 128, p;\nselp.u32 %0, %4, 1, r;\n}"
                       : "=r"(unsafe) : "f"(fmin_nan(sum0, sum1)), "f"(fmax_nan(sum0, sum1)), "r"(4 + w), "r"(reloaded) : "memory");
        const float l0 = rcp(sum0), l1 = rcp(sum1);
        uint32_t u[8];
#pragma unroll
        for (int j = 0; j < 4; j++) {
          u[j] = pack(o[4 * j] * l0, o[4 * j + 1] * l0);
          u[4 + j] = pack(o[4 * j + 2] * l1, o[4 * j + 3] * l1);
        }
        const int xsrc = (lane & 28) | (2 * hh + (q >> 1));
        const uint32_t x0 = __shfl_sync(0xffffffffu, u[3], xsrc), x1 = __shfl_sync(0xffffffffu, u[7], xsrc), ps = 0x7610 + (q & 1) * 0x22;
        st_ll_if(!unsafe, op + 65536 * hh, u[0], u[4], u[1], tag_lo(u[5], otag));
        st_ll_if(!unsafe, op + 65536 * hh + 32, __byte_perm(x0, otag, ps), __byte_perm(x1, u[5], ps), u[2], u[6]);
        mbar_arrive_if(hh == 0 && !unsafe && lane == 0, bar(B_U0));
        TSH(w, 15 + 4 * hh, 15);
        return __any_sync(0xffffffffu, unsafe);
      };
      int redo_from;
      bool use_max = true;
      pin<8>(qa); pin<8>(qb);
      scores_a(qa, 0); scores_b(qa, 0);
      if (w) mbar_wait_tma(bar(B_E));
      wg_wait0();
      pin<96>(s + 32);
      TSH(w, 13, 13);
      softmax_pv(0, false, 0.f, 0.f, true);
      scores_a(qb, 1);
      const bool bad0 = finish(0, true, reload);
      scores_b(qb, 1);
      if (bad0) {
        wg_wait0();
        pin<96>(s + 32);
        redo_from = 0;
        use_max = !__any_sync(0xffffffffu, reload);
      } else {
        mbar_wait_tma(bar(B_E + 1 + w));
        wg_wait0();
        pin<96>(s + 32);
        TSH(w, 17, 13);
        softmax_pv(1, false, 0.f, 0.f, w == 0);
        redo_from = finish(1, true, 0) ? 1 : 2;
      }
      int handed = redo_from;
#pragma unroll 1
      for (int hh = redo_from; hh < 2;) {
        if (hh) {
#pragma unroll
          for (int i = 0; i < 8; i++) qa[i] = qb[i];
        }
        pin<8>(qa);
        scores_a(qa, hh); scores_b(qa, hh);
        wg_wait0();
        pin<96>(s + 32);
        float m0 = 0.f, m1 = 0.f;
        if (use_max) {
          float m2 = fmaxf(sd[4], sd[5]), m3 = fmaxf(sd[6], sd[7]);
          m0 = fmaxf(sd[0], sd[1]); m1 = fmaxf(sd[2], sd[3]);
          acc_max<24>(sd + 8, m0, m1, m2, m3);
          acc_max<96>(s + 32, m0, m1, m2, m3);
          m0 = fmaxf(m0, m2); m1 = fmaxf(m1, m3);
          m0 = fmaxf(m0, shfl_x(m0, 1)); m1 = fmaxf(m1, shfl_x(m1, 1));
          m0 = fmaxf(m0, shfl_x(m0, 2)); m1 = fmaxf(m1, shfl_x(m1, 2));
        }
        softmax_pv(hh, true, m0, m1, hh > handed && w == 0);
        handed = hh;
        if (finish(hh, !use_max, 0)) use_max = true;
        else hh++;
      }
    }
    const uint32_t o_sp = OFF(o[1][2 * m + w][lane & 7][wi][1][31]), a_os = sb + 1024 * wi + 16 * lane;
    int spins = 0;
    uint32_t redo;
#pragma unroll 1
    do {
      uint4 v[32];
      TSB(w, 2);
#pragma unroll
      for (int i = 12; i < 16; i++) v[i] = ld_ll(ip + 256 * (i >> 1) + 32 * (i & 1));
      const uint32_t* sp = (const uint32_t*)(scb + o_sp);
      const uint64_t db = mkdesc(__shfl_sync(0xffffffffu, sb + (g & 1) * 16, 0));
      if (spins == 0) {
        const uint32_t a0 = a_os + (w ? 40960 : R_V), a1 = a_os + (w ? 40960 : 16384);
        mbar_wait(bar(B_OS0 + w));
        static_for<0, 12>([&](auto I) { constexpr int i = decltype(I)::v; v[i] = lds128i<4096 * (i >> 1) + 512 * (i & 1)>(i < 8 ? a0 : a1); });
      } else {
#pragma unroll
        for (int i = 0; i < 12; i++) v[i] = ld_ll(ip + 256 * (i >> 1) + 32 * (i & 1));
      }
      uint32_t bad = 0, bad2 = 0;
#pragma unroll
      for (int i = 0; i < 16; i += 2) { bad |= v[i].w ^ otag; bad2 |= v[i + 1].x ^ otag; }
      bad = keep(bad | bad2); bad2 = 0;
#pragma unroll 1
      while (__any_sync(0xffffffffu, (ld_relaxed(sp) ^ otag) > 0xffffu) && ++spins < SPIN_LIMIT) {}
      TS(w, 12);
#pragma unroll
      for (int i = 0; i < 16; i++) v[16 + i] = ld_ll(ip + 65536 + 256 * (i >> 1) + 32 * (i & 1));
      TSB(w, 3);
      mbar_wait(bar(B_WO));
      TSB(w, 4);
#pragma unroll
      for (int i = 0; i < 16; i++) {
        const int st = i >> 3, gg = i & 7, mo = (st ? R_M1 : R_M0) + gg * 1024, ma = R_Q + st * 24576 + gg * 3072;
        uint4* u = v + 2 * i;
        if (i == 0 || i == 8) wg_fence();
        wg_n56_t(hv, u[0].x, u[0].y, u[0].z, u[0].w, db + ma / 16, i > 0);
        wg_n56_t(hv, u[1].x, u[1].y, u[1].z, u[1].w, db + mo / 16 + ((uint64_t)((ma + 1024 - mo) / 16) << 32), 1);
        if (i == 7) TSB(w, 5);
        if (i == 8) TSB(w, 6);
      }
      TS(w, 20);
      wg_commit();
      mbar_wait(bar(B_XS));
      const uint32_t a_xs = sb + X_SL + (16 * warp + (lane & 7)) * 128 + ((((lane >> 3) + (g & 1)) ^ lane) & 7) * 16;
      o_so = keep(OFF(stats[tile][g][r8])); o_si = keep(OFF(stats[tile][4 * (q & 1)][rloc]));
      o_cp = keep(OFF(crow[2 * tile][0][g][q])); inv_tok = keep(2 * (2047 - row0 - rloc));
      ldsm4(a_xs, xs); ldsm4(a_xs ^ 64, xs + 4); ldsm4(a_xs + 1024, xs + 8); ldsm4((a_xs ^ 64) + 1024, xs + 12);
#pragma unroll
      for (int j = 0; j < 7; j++) bw[j] = sel(r8 == 0, 0x3f803f80u, ((const volatile uint32_t*)(smem + R_WR))[4 * j + q]);
      wsum = ((const volatile float*)(smem + R_WR))[28];
#pragma unroll
      for (int i = 16; i < 32; i += 2) { bad |= v[i].w ^ otag; bad2 |= v[i + 1].x ^ otag; }
      asm volatile("{\n.reg .pred p, r;\nsetp.gt.u32 p, %1, 0xffff;\nbar.red.or.pred r, %2, 128, p;\nselp.u32 %0, 1, 0, r;\n}"
                   : "=r"(redo) : "r"(bad | bad2), "r"(4 + w) : "memory");
      wg_wait0();
      pin<28>(hv);
    } while (redo && ++spins < SPIN_LIMIT);
  }
  TS(w, 21);

  uint32_t hk[14], nk[14];
  uint32_t wa[28], wb[16];
  {
#pragma unroll
    for (int j = 0; j < 7; j++) {
      hk[2 * j] = add_bf2(xs[j], pack(hv[4 * j], hv[4 * j + 1]));
      hk[2 * j + 1] = add_bf2(xs[8 + j], pack(hv[4 * j + 2], hv[4 * j + 3]));
    }
    float c[6][4];
#pragma unroll
    for (int i = 0; i < 24; i++) c[i >> 2][i & 3] = 0.f;
#pragma unroll
    for (int j = 0; j < 7; j++) {
      mma1688(c[j & 1], hk[2 * j], hk[2 * j + 1], bw[j]);
      mma1688(c[2 + (j & 1)], hk[2 * j], hk[2 * j + 1], hk[2 * j]);
      mma1688(c[4 + (j & 1)], hk[2 * j], hk[2 * j + 1], hk[2 * j + 1]);
    }
    const float q0 = __shfl_sync(0xffffffffu, bsel ? c[2][1] + c[3][1] : c[2][0] + c[3][0], dsrc);
    const float q1 = __shfl_sync(0xffffffffu, bsel ? c[4][3] + c[5][3] : c[4][2] + c[5][2], dsrc);
    st_ll_if(q == 0, scb + o_so, __float_as_uint(c[0][0] + c[1][0]), __float_as_uint(c[0][1] + c[1][1]), __float_as_uint(q0), epoch);
    st_ll_if(q == 0, scb + o_so + 128, __float_as_uint(c[0][2] + c[1][2]), __float_as_uint(c[0][3] + c[1][3]), __float_as_uint(q1), epoch);
    TSB(w, 7);
    {
      o_rp = keep(OFF(rec[g][tile]));
      a_ci = keep(sb + SMALL + 4096 + 1024 * bsel + 256 * (warp >> 1) + 16 * q);
      o_pp = keep(OFF(part[16 * warp + 4 * q + (r8 >> 1)][cta][r8 & 1]));
      o_gp = keep(OFF(part[cta][lane >> 1][lane & 1]));
      f1w = keep(sb + SMALL + 4 * (64 + 32 * warp + 16 * (q & 1) + 4 * (r8 >> 1) + (r8 & 1) + (q & 2)));
      f1r = keep(sb + SMALL + 4 * (64 + 16 * bsel + 4 * q));
      const uint32_t kr = (lane & 7) + 8 * (lane >> 4), ch = (lane >> 3) & 1;
      a_wa = keep(sb + R_F + (warp & 1) * 14336 + (112 * (warp >> 1) + kr) * 32 + (ch ^ ((lane >> 2) & 1)) * 16);
      a_wb = keep(sb + R_F + 28672 + 2048 * min(warp, 6) + kr * 128 + (ch ^ (lane & 7)) * 16);
      a_st = keep(sb + X_SL + 2048 * warp + (lane & 7) * 112 + (lane >> 3) * 16);
    }
#pragma unroll
    for (int j = 0; j < 7; j++) {
      hv[4 * j] = lo_f(hk[2 * j]); hv[4 * j + 1] = hi_f(hk[2 * j]); hv[4 * j + 2] = lo_f(hk[2 * j + 1]); hv[4 * j + 3] = hi_f(hk[2 * j + 1]);
    }
    pin<28>(hv);
    uint4 u[4];
    int spins = 0;
#pragma unroll 1
    do {
#pragma unroll
      for (int i = 0; i < 4; i++) u[i] = ld_ll(scb + o_si + 256 * i);
    } while (__any_sync(0xffffffffu, (((u[0].w ^ epoch) | (u[1].w ^ epoch)) | ((u[2].w ^ epoch) | (u[3].w ^ epoch))) != 0) && ++spins < SPIN_LIMIT);
    TS(w, 22);
    float s1 = (__uint_as_float(u[0].x) + __uint_as_float(u[1].x)) + (__uint_as_float(u[2].x) + __uint_as_float(u[3].x));
    float s3 = (__uint_as_float(u[0].y) + __uint_as_float(u[1].y)) + (__uint_as_float(u[2].y) + __uint_as_float(u[3].y));
    float s2 = (__uint_as_float(u[0].z) + __uint_as_float(u[1].z)) + (__uint_as_float(u[2].z) + __uint_as_float(u[3].z));
    s1 += shfl_x(s1, 1); s2 += shfl_x(s2, 1); s3 += shfl_x(s3, 1);
    const float mu = s1 * (1.f / D_);
    float rs;
    asm("rsqrt.approx.ftz.f32 %0, %1;" : "=f"(rs) : "f"(fmaxf(fmaf(s2, 1.f / D_, -mu * mu), 0.f) + 1e-5f));
    uint32_t k1, k2;
    top2(to_key(rs * fmaf(-mu, wsum, s3), inv_tok), k1, k2);
    st_ll_if(lane == 0, scb + o_rp, k1, k2 | 1, 0, epoch);
    mbar_arrive_if(lane == 0, bar(B_S1));
    const bool up = q >= 2;
    const float nb = -mu * rs;
    const float rsx = shfl_x(rs, 2), nbx = shfl_x(nb, 2);
    const float rs0 = up ? rsx : rs, rs1 = up ? rs : rsx, nb0 = up ? nbx : nb, nb1 = up ? nb : nbx;
#pragma unroll
    for (int j = 0; j < 7; j++) {
      nk[2 * j] = pack(fmaf(hv[4 * j], rs0, nb0), fmaf(hv[4 * j + 1], rs0, nb0));
      nk[2 * j + 1] = pack(fmaf(hv[4 * j + 2], rs1, nb1), fmaf(hv[4 * j + 3], rs1, nb1));
    }
    const uint32_t d1 = key_token(k1) & 15, d2 = key_token(k2) & 15;
#pragma unroll
    for (int a = 0; a < 2; a++) {
#pragma unroll
      for (int h = 0; h < 2; h++) {
        const uint32_t* k = (a ? hk : nk) + h;
        const bool on = d1 == r8 + 8 * h || d2 == r8 + 8 * h;
        char* p = scb + o_cp + (d2 == r8 + 8 * h ? 2048 : 0) + 1024 * a;
        st_ll_if(on, p, k[0], k[2], k[4], tag_lo(k[6], tag_hi));
        st_ll_if(on, p + 64, k[8], k[10], k[12], tag_up(k[6], tag_hi));
      }
    }
  }
  TS(w, 23);
  {
    if (cta < NFFN) mbar_wait(bar(B_FF));
#pragma unroll
    for (int i = 0; i < 7; i++) ldsm4t(a_wa + 512 * i, wa + 4 * i);
#pragma unroll
    for (int i = 0; i < 4; i++) ldsm4t(a_wb ^ (32 * i), wb + 4 * i);
    const uint32_t base = a_st;
    __syncwarp();
    uint32_t k[14];
#pragma unroll
    for (int j = 0; j < 14; j++) k[j] = add_bf2(hk[j], nk[j]);
    stsm4(base, k[0], k[2], k[4], k[6]);
    stsm4(base + 896, k[1], k[3], k[5], k[7]);
    stsm4(base + 48, k[6], k[8], k[10], k[12]);
    stsm4(base + 944, k[7], k[9], k[11], k[13]);
    __syncwarp();
    if (cta >= NFFN) { if (lane == 0) mbar_arrive(bar(B_WIN)); }
    else {
      TSB(w, 8);
      mbar_wait(bar(B_ROW));
      TS(w, 24);
      uint4 t[4];
#pragma unroll
      for (int i = 0; i < 4; i++) { const float4 f = lds128(a_ci + 64 * i); t[i] = make_uint4(__float_as_uint(f.x), __float_as_uint(f.y), __float_as_uint(f.z), __float_as_uint(f.w)); }
      const uint32_t kk[14] = {t[0].x, t[0].y, t[0].z, untag(t[0].w, t[1].w), t[1].x, t[1].y, t[1].z,
                               t[2].x, t[2].y, t[2].z, untag(t[2].w, t[3].w), t[3].x, t[3].y, t[3].z};
      float c[4] = {0.f, 0.f, 0.f, 0.f}, d[4] = {0.f, 0.f, 0.f, 0.f};
#pragma unroll
      for (int i = 0; i < 7; i++) mma16816((i & 1) ? d : c, wa[4 * i], wa[4 * i + 1], wa[4 * i + 2], wa[4 * i + 3], kk[2 * i], kk[2 * i + 1]);
      const float z = self(q & 2, self(q & 1, c[3], c[2]) + self(q & 1, d[3], d[2]), self(q & 1, c[1], c[0]) + self(q & 1, d[1], d[0]));
      asm volatile("st.shared.f32 [%0], %1;" ::"r"(f1w), "f"(z) : "memory");
      __syncwarp();
      if (lane == 0) mbar_arrive(bar(B_S2));
      if (warp < 7) {
        mbar_wait(bar(B_S2));
        TS(w, 25);
        float4 pa[8];
#pragma unroll
        for (int k = 0; k < 8; k++) pa[k] = lds128(f1r + 128 * k);
        float4 gs = pa[0], us = pa[1];
#pragma unroll
        for (int k = 1; k < 4; k++) {
          const float4 a = pa[2 * k], b = pa[2 * k + 1];
          gs.x += a.x; gs.y += a.y; gs.z += a.z; gs.w += a.w; us.x += b.x; us.y += b.y; us.z += b.z; us.w += b.w;
        }
        const uint32_t g0 = pack(gs.x, gs.y), g1 = pack(gs.z, gs.w), u0 = pack(us.x, us.y), u1 = pack(us.z, us.w);
        auto silu = [](float v) { return v * rcp(1.f + ex2(-1.4426950408889634f * v)); };
        const uint32_t b0 = mul_bf2(pack(silu(lo_f(g0)), silu(hi_f(g0))), u0), b1 = mul_bf2(pack(silu(lo_f(g1)), silu(hi_f(g1))), u1);
        float e[4][4];
#pragma unroll
        for (int i = 0; i < 4; i++) {
          e[i][0] = e[i][1] = e[i][2] = e[i][3] = 0.f;
          mma16816(e[i], wb[4 * i], wb[4 * i + 1], wb[4 * i + 2], wb[4 * i + 3], b0, b1);
        }
        float y[4];
#pragma unroll
        for (int i = 0; i < 4; i++) y[i] = (q & 2) ? ((q & 1) ? e[3][i] : e[2][i]) : ((q & 1) ? e[1][i] : e[0][i]);
        st_ll(scb + o_pp, __float_as_uint(y[0]), __float_as_uint(y[1]), __float_as_uint(y[2]), (__float_as_uint(y[3]) & ~15u) | (epoch & 15u));
      }
      TS(w, 26);
      if (lane == 0) mbar_arrive(bar(B_WIN));
    }
  }
  if (cta < NFFN && warp == 7) {
    mbar_wait(bar(B_FIN));
    const float4 fin = lds128(sb + SMALL + 2048 + 16 * (lane & 7));
    __nv_bfloat16* outp = P.out + __float_as_uint(fin.w);
    mbar_wait(bar(B_WIN));
    int spins = 0;
    uint4 pu[7];
    uint32_t bad;
#pragma unroll 1
    do {
      bad = 0;
#pragma unroll
      for (int i = 0; i < 7; i++) pu[i] = ld_ll(scb + o_gp + 512 * i);
#pragma unroll
      for (int i = 0; i < 7; i++) bad |= pu[i].w ^ epoch;
    } while (__any_sync(0xffffffffu, (bad & 15u) != 0) && ++spins < SPIN_LIMIT);
    float y[4];
#pragma unroll
    for (int c = 0; c < 4; c++) {
      float t[7];
#pragma unroll
      for (int i = 0; i < 7; i++) t[i] = __uint_as_float(c == 0 ? pu[i].x : (c == 1 ? pu[i].y : (c == 2 ? pu[i].z : pu[i].w & ~15u)));
      y[c] = ((t[0] + t[1]) + (t[2] + t[3])) + ((t[4] + t[5]) + t[6]);
    }
    const bool s1 = lane & 2, s2 = lane & 4;
    const float z0 = (s1 ? y[1] : y[0]) + shfl_x(s1 ? y[0] : y[1], 2), z2 = (s1 ? y[3] : y[2]) + shfl_x(s1 ? y[2] : y[3], 2);
    float z = (s2 ? z2 : z0) + shfl_x(s2 ? z0 : z2, 4);
    z += shfl_x(z, 8); z += shfl_x(z, 16);
    if (lane < 8) *outp = __float2bfloat16_rn(fin.y + rbf(fin.x + rbf(rbf(z) * fin.z)));
    if (cta == 0 && lane == 0) st_relaxed(&sc->epoch[0], epoch);
  }
  TSDUMP();
}

typedef CUresult (*EncodeFn)(CUtensorMap*, CUtensorMapDataType, cuuint32_t, void*, const cuuint64_t*, const cuuint64_t*,
                             const cuuint32_t*, const cuuint32_t*, CUtensorMapInterleave, CUtensorMapSwizzle,
                             CUtensorMapL2promotion, CUtensorMapFloatOOBfill);

CUtensorMap make_map(EncodeFn enc, const void* p, int rank, const cuuint64_t* dims, const cuuint64_t* strides,
                     const cuuint32_t* box, CUtensorMapSwizzle sw) {
  CUtensorMap m;
  const cuuint32_t es[5] = {1, 1, 1, 1, 1};
  enc(&m, CU_TENSOR_MAP_DATA_TYPE_BFLOAT16, rank, const_cast<void*>(p), dims, strides, box, es, CU_TENSOR_MAP_INTERLEAVE_NONE, sw,
      CU_TENSOR_MAP_L2_PROMOTION_NONE, CU_TENSOR_MAP_FLOAT_OOB_FILL_NONE);
  return m;
}
CUtensorMap make_map2(EncodeFn enc, const void* p, int cols, int rows, int bc, int br, CUtensorMapSwizzle sw) {
  const cuuint64_t dims[2] = {(cuuint64_t)cols, (cuuint64_t)rows}, strides[1] = {(cuuint64_t)cols * 2};
  const cuuint32_t box[2] = {(cuuint32_t)bc, (cuuint32_t)br};
  return make_map(enc, p, 2, dims, strides, box, sw);
}

}

extern "C" void kernel_launch(void* const* d_in, const int* in_sizes, int n_in, void* d_out, int out_size) {
  (void)in_sizes; (void)n_in; (void)out_size;
  static EncodeFn enc = nullptr;
  static Scratch* sc = nullptr;
  if (!enc) {
    void* fn = nullptr;
    cudaDriverEntryPointQueryResult qr;
    cudaGetDriverEntryPoint("cuTensorMapEncodeTiled", &fn, cudaEnableDefault, &qr);
    enc = (EncodeFn)fn;
    cudaGetSymbolAddress((void**)&sc, g_sc);
    cudaFuncSetAttribute(fused_block_kernel, cudaFuncAttributeMaxDynamicSharedMemorySize, SMEM_BYTES);
  }
  Params P;
  P.x = (const __nv_bfloat16*)d_in[0];  P.wqkv = (const __nv_bfloat16*)d_in[1];  P.wo = (const __nv_bfloat16*)d_in[2]; P.wr = (const __nv_bfloat16*)d_in[4];
  P.wg = (const __nv_bfloat16*)d_in[5]; P.wu = (const __nv_bfloat16*)d_in[6]; P.wd = (const __nv_bfloat16*)d_in[7];
  P.out = (__nv_bfloat16*)d_out; P.sc = sc;
  const CUtensorMap tm_w = make_map2(enc, d_in[1], 3 * D_, D_, 64, 112, CU_TENSOR_MAP_SWIZZLE_128B);
  const cuuint64_t od3[3] = {448, 56, 8}, os3[2] = {896, 56 * 896};
  const cuuint32_t ob3[3] = {64, 24, 8};
  const CUtensorMap tm_wo = make_map(enc, P.wo, 3, od3, os3, ob3, CU_TENSOR_MAP_SWIZZLE_128B);
  const CUtensorMap tm_x = make_map2(enc, P.x, D_, S_, 64, 128, CU_TENSOR_MAP_SWIZZLE_128B);
  const cuuint64_t dd3[3] = {64, F_, 7}, ds3[2] = {896, 128};
  const cuuint32_t db3[3] = {64, 16, 7};
  const CUtensorMap tm_d = make_map(enc, P.wd, 3, dd3, ds3, db3, CU_TENSOR_MAP_SWIZZLE_128B);
  fused_block_kernel<<<NCTA, NTHREADS, SMEM_BYTES, cudaStreamPerThread>>>(P, tm_x, tm_w, tm_wo, tm_d);
}
```

```cpp
#include <cuda_runtime.h>
#include <cuda_bf16.h>
#include <cuda.h>
#include <stdint.h>

#define FTMA 0
namespace {

constexpr int S_ = 2048, D_ = 448, F_ = 1792;
constexpr int NCTA = 128, NFFN = 112, NTHREADS = 384;
constexpr int SPIN_LIMIT = 1 << 18;

constexpr uint32_t R_K = 0;
constexpr uint32_t R_V = 73728;
__host__ __device__ constexpr uint32_t rem_off(int kv, int hh) { return kv ? R_V + 16384 * hh : (hh ? 16384 : 40960); }
__host__ __device__ constexpr uint32_t own_off(int kv, int hh) { return kv ? (hh ? 0 : 32768) : 57344 + 8192 * hh; }
constexpr uint32_t X_SL = R_V + 32768;
constexpr uint32_t R_Q = 131072;
constexpr uint32_t R_M0 = 8192, R_M1 = X_SL + 16384;
constexpr uint32_t R_F = 188416;
constexpr uint32_t R_BAR = 231424;
constexpr uint32_t R_WR = R_BAR + 416;
constexpr uint32_t SMALL = R_Q + 49152;
constexpr uint32_t SMEM_BYTES = R_BAR + 1024;

__host__ __device__ constexpr uint32_t x_off(int c) { return c == 0 ? 57344 : 114688 + 16384 * c; }
__host__ __device__ constexpr uint32_t sec_off(int p) { return p == 0 ? R_K : (p == 1 ? R_V : R_Q); }
enum { B_X = 0, B_W = 7, B_KL = 19, B_VL = B_KL + 2, B_KR = B_VL + 2, B_VR, B_OS0, B_OS1, B_ROW, B_FIN, B_WO, B_KVF, B_FF, B_XS, B_KD0, B_KD1, B_VD0, B_VD1, B_QD0, B_QD1, B_CN, B_E, B_XC = B_E + 3, B_U0, B_WIN, B_S1, B_S2, B_COUNT };
__host__ __device__ constexpr int bar_count(int i) { return i < B_WO ? 1 : (i <= B_XS ? 2 : (i < B_XC ? 4 : 8)); }

struct __align__(1024) Scratch {
  uint4 kv[32][8][2][2][256];
  uint4 o[2][32][8][4][2][32];
  uint4 stats[128][8][16];
  uint4 part[NFFN][NFFN][2];
  uint4 crow[256][2][8][8];
  uint4 rec[8][128];
  uint32_t epoch[8];
};
__device__ Scratch g_sc;

struct Params {
  const __nv_bfloat16* x; const __nv_bfloat16* wqkv; const __nv_bfloat16* wo; const __nv_bfloat16* wr;
  const __nv_bfloat16* wg; const __nv_bfloat16* wu; const __nv_bfloat16* wd;
  __nv_bfloat16* out; Scratch* sc;
};

__device__ __forceinline__ void wg_n56_t(float* d, uint32_t a0, uint32_t a1, uint32_t a2, uint32_t a3, uint64_t db, int scale_d) {
  asm volatile("{\n.reg .pred p;\nsetp.ne.b32 p, %33, 0;\n"
    "wgmma.mma_async.sync.aligned.m64n56k16.f32.bf16.bf16 "
    "{%0,%1,%2,%3,%4,%5,%6,%7,%8,%9,%10,%11,%12,%13,%14,%15,%16,%17,%18,%19,%20,%21,%22,%23,%24,%25,%26,%27"
    "}, {%28,%29,%30,%31}, %32, p, 1, 1, 1;\n}\n"
    : "+f"(d[0]), "+f"(d[1]), "+f"(d[2]), "+f"(d[3]), "+f"(d[4]), "+f"(d[5]), "+f"(d[6]), "+f"(d[7]),
      "+f"(d[8]), "+f"(d[9]), "+f"(d[10]), "+f"(d[11]), "+f"(d[12]), "+f"(d[13]), "+f"(d[14]), "+f"(d[15]),
      "+f"(d[16]), "+f"(d[17]), "+f"(d[18]), "+f"(d[19]), "+f"(d[20]), "+f"(d[21]), "+f"(d[22]), "+f"(d[23]),
      "+f"(d[24]), "+f"(d[25]), "+f"(d[26]), "+f"(d[27])
      : "r"(a0), "r"(a1), "r"(a2), "r"(a3), "l"(db), "r"(scale_d));
}
__device__ __forceinline__ void wg_n32_t(float* d, uint32_t a0, uint32_t a1, uint32_t a2, uint32_t a3, uint64_t db, int scale_d) {
  asm volatile("{\n.reg .pred p;\nsetp.ne.b32 p, %21, 0;\n"
    "wgmma.mma_async.sync.aligned.m64n32k16.f32.bf16.bf16 "
    "{%0,%1,%2,%3,%4,%5,%6,%7,%8,%9,%10,%11,%12,%13,%14,%15"
    "}, {%16,%17,%18,%19}, %20, p, 1, 1, 1;\n}\n"
    : "+f"(d[0]), "+f"(d[1]), "+f"(d[2]), "+f"(d[3]), "+f"(d[4]), "+f"(d[5]), "+f"(d[6]), "+f"(d[7]),
      "+f"(d[8]), "+f"(d[9]), "+f"(d[10]), "+f"(d[11]), "+f"(d[12]), "+f"(d[13]), "+f"(d[14]), "+f"(d[15])
      : "r"(a0), "r"(a1), "r"(a2), "r"(a3), "l"(db), "r"(scale_d));
}
__device__ __forceinline__ void wg_n64(float* d, uint32_t a0, uint32_t a1, uint32_t a2, uint32_t a3, uint64_t db, int scale_d) {
  asm volatile("{\n.reg .pred p;\nsetp.ne.b32 p, %37, 0;\n"
    "wgmma.mma_async.sync.aligned.m64n64k16.f32.bf16.bf16 "
    "{%0,%1,%2,%3,%4,%5,%6,%7,%8,%9,%10,%11,%12,%13,%14,%15,%16,%17,%18,%19,%20,%21,%22,%23,%24,%25,%26,%27,%28,%29,%30,%31"
    "}, {%32,%33,%34,%35}, %36, p, 1, 1, 0;\n}\n"
    : "+f"(d[0]), "+f"(d[1]), "+f"(d[2]), "+f"(d[3]), "+f"(d[4]), "+f"(d[5]), "+f"(d[6]), "+f"(d[7]),
      "+f"(d[8]), "+f"(d[9]), "+f"(d[10]), "+f"(d[11]), "+f"(d[12]), "+f"(d[13]), "+f"(d[14]), "+f"(d[15]),
      "+f"(d[16]), "+f"(d[17]), "+f"(d[18]), "+f"(d[19]), "+f"(d[20]), "+f"(d[21]), "+f"(d[22]), "+f"(d[23]),
      "+f"(d[24]), "+f"(d[25]), "+f"(d[26]), "+f"(d[27]), "+f"(d[28]), "+f"(d[29]), "+f"(d[30]), "+f"(d[31])
      : "r"(a0), "r"(a1), "r"(a2), "r"(a3), "l"(db), "r"(scale_d));
}
__device__ __forceinline__ void wg_n128(float* d, uint32_t a0, uint32_t a1, uint32_t a2, uint32_t a3, uint64_t db, int scale_d) {
  asm volatile("{\n.reg .pred p;\nsetp.ne.b32 p, %69, 0;\n"
    "wgmma.mma_async.sync.aligned.m64n128k16.f32.bf16.bf16 "
    "{%0,%1,%2,%3,%4,%5,%6,%7,%8,%9,%10,%11,%12,%13,%14,%15,%16,%17,%18,%19,%20,%21,%22,%23,%24,%25,%26,%27,%28,%29,%30,%31,"
    "%32,%33,%34,%35,%36,%37,%38,%39,%40,%41,%42,%43,%44,%45,%46,%47,%48,%49,%50,%51,%52,%53,%54,%55,%56,%57,%58,%59,%60,%61,%62,%63"
    "}, {%64,%65,%66,%67}, %68, p, 1, 1, 0;\n}\n"
    : "+f"(d[0]), "+f"(d[1]), "+f"(d[2]), "+f"(d[3]), "+f"(d[4]), "+f"(d[5]), "+f"(d[6]), "+f"(d[7]),
      "+f"(d[8]), "+f"(d[9]), "+f"(d[10]), "+f"(d[11]), "+f"(d[12]), "+f"(d[13]), "+f"(d[14]), "+f"(d[15]),
      "+f"(d[16]), "+f"(d[17]), "+f"(d[18]), "+f"(d[19]), "+f"(d[20]), "+f"(d[21]), "+f"(d[22]), "+f"(d[23]),
      "+f"(d[24]), "+f"(d[25]), "+f"(d[26]), "+f"(d[27]), "+f"(d[28]), "+f"(d[29]), "+f"(d[30]), "+f"(d[31]),
      "+f"(d[32]), "+f"(d[33]), "+f"(d[34]), "+f"(d[35]), "+f"(d[36]), "+f"(d[37]), "+f"(d[38]), "+f"(d[39]),
      "+f"(d[40]), "+f"(d[41]), "+f"(d[42]), "+f"(d[43]), "+f"(d[44]), "+f"(d[45]), "+f"(d[46]), "+f"(d[47]),
      "+f"(d[48]), "+f"(d[49]), "+f"(d[50]), "+f"(d[51]), "+f"(d[52]), "+f"(d[53]), "+f"(d[54]), "+f"(d[55]),
      "+f"(d[56]), "+f"(d[57]), "+f"(d[58]), "+f"(d[59]), "+f"(d[60]), "+f"(d[61]), "+f"(d[62]), "+f"(d[63])
      : "r"(a0), "r"(a1), "r"(a2), "r"(a3), "l"(db), "r"(scale_d));
}

__device__ __forceinline__ void wg_fence() { asm volatile("wgmma.fence.sync.aligned;" ::: "memory"); }
__device__ __forceinline__ void wg_commit() { asm volatile("wgmma.commit_group.sync.aligned;" ::: "memory"); }
__device__ __forceinline__ void wg_wait0() { asm volatile("wgmma.wait_group.sync.aligned 0;" ::: "memory"); }
__device__ __forceinline__ void wg_wait1() { asm volatile("wgmma.wait_group.sync.aligned 1;" ::: "memory"); }
template <int N> __device__ __forceinline__ void pin(float* d) {
#pragma unroll
  for (int i = 0; i < N; i++) asm volatile("" : "+f"(d[i])::"memory");
}
template <int N> __device__ __forceinline__ void pin(uint32_t* d) {
#pragma unroll
  for (int i = 0; i < N; i++) asm volatile("" : "+r"(d[i])::"memory");
}
__device__ __forceinline__ uint64_t mkdesc(uint32_t addr) {
  return (uint64_t)((addr & 0x3FFFF) >> 4) | (1ull << 16) | (64ull << 32) | (1ull << 62);
}
__device__ __forceinline__ uint64_t mkdesc64(uint32_t addr) {
  return (uint64_t)((addr & 0x3FFFF) >> 4) | (1ull << 16) | (32ull << 32) | (2ull << 62);
}
__device__ __forceinline__ void mbar_init(uint32_t a, int c) { asm volatile("mbarrier.init.shared::cta.b64 [%0], %1;" ::"r"(a), "r"(c) : "memory"); }
__device__ __forceinline__ void mbar_expect(uint32_t a, int b) { asm volatile("mbarrier.arrive.expect_tx.shared::cta.b64 _, [%0], %1;" ::"r"(a), "r"(b) : "memory"); }
__device__ __forceinline__ void mbar_arrive(uint32_t a) { asm volatile("mbarrier.arrive.shared::cta.b64 _, [%0];" ::"r"(a) : "memory"); }
__device__ __forceinline__ void mbar_arrive_if(bool on, uint32_t a) {
  asm volatile("{\n.reg .pred p;\nsetp.ne.u32 p, %1, 0;\n@p mbarrier.arrive.shared::cta.b64 _, [%0];\n}" ::"r"(a), "r"((uint32_t)on) : "memory");
}
__device__ __forceinline__ void mbar_wait(uint32_t a, uint32_t parity = 0) {
  asm volatile("{\n.reg .pred p;\n.reg .u32 n;\nmov.u32 n, 0;\n"
               "W_%=:\nmbarrier.try_wait.parity.shared::cta.b64 p, [%0], %1;\n@p bra D_%=;\n"
               "add.u32 n, n, 1;\nsetp.lt.u32 p, n, 1048576;\n@p bra W_%=;\nD_%=:\n}" ::"r"(a), "r"(parity) : "memory");
}
__device__ __forceinline__ bool mbar_test(uint32_t a) {
  uint32_t r;
  asm volatile("{\n.reg .pred p;\nmbarrier.test_wait.parity.shared::cta.b64 p, [%1], 0;\nselp.u32 %0, 1, 0, p;\n}" : "=r"(r) : "r"(a) : "memory");
  return r;
}
__device__ __forceinline__ void mbar_wait_tma(uint32_t a) {
  asm volatile("{\n.reg .pred p;\nW_%=:\nmbarrier.try_wait.parity.shared::cta.b64 p, [%0], 0;\n@!p bra W_%=;\n}" ::"r"(a) : "memory");
}
__device__ __forceinline__ void bar_sync(int id, int n) { asm volatile("bar.sync %0, %1;" ::"r"(id), "r"(n) : "memory"); }
__device__ __forceinline__ void bar_arrive(int id, int n) { asm volatile("bar.arrive %0, %1;" ::"r"(id), "r"(n) : "memory"); }
__device__ __forceinline__ void fence_async_smem() { asm volatile("fence.proxy.async.shared::cta;" ::: "memory"); }
__device__ __forceinline__ bool elect() {
  uint32_t p;
  asm volatile("{\n.reg .pred p;\nelect.sync _|p, 0xffffffff;\nselp.u32 %0, 1, 0, p;\n}" : "=r"(p));
  return p;
}
__device__ __forceinline__ void tma2d(uint32_t dst, const CUtensorMap* m, int c0, int c1, uint32_t bar) {
  asm volatile("cp.async.bulk.tensor.2d.shared::cluster.global.mbarrier::complete_tx::bytes [%0], [%1, {%3, %4}], [%2];"
               ::"r"(dst), "l"(m), "r"(bar), "r"(c0), "r"(c1) : "memory");
}
__device__ __forceinline__ void tma3d(uint32_t dst, const CUtensorMap* m, int c0, int c1, uint32_t bar) {
  asm volatile("cp.async.bulk.tensor.3d.shared::cluster.global.mbarrier::complete_tx::bytes [%0], [%1, {%3, %4, %5}], [%2];"
               ::"r"(dst), "l"(m), "r"(bar), "r"(c0), "r"(c1), "r"(0) : "memory");
}
__device__ __forceinline__ void bulk_load(uint32_t dst, const void* src, int bytes, uint32_t bar) {
  asm volatile("cp.async.bulk.shared::cluster.global.mbarrier::complete_tx::bytes [%0], [%1], %2, [%3];"
               ::"r"(dst), "l"(src), "r"(bytes), "r"(bar) : "memory");
}
__device__ __forceinline__ void bulk_store(void* dst, uint32_t src, int bytes) {
  asm volatile("cp.async.bulk.global.shared::cta.bulk_group [%0], [%1], %2;" ::"l"(dst), "r"(src), "r"(bytes) : "memory");
}
__device__ __forceinline__ uint32_t ld_relaxed(const uint32_t* p) {
  uint32_t v;
  asm volatile("ld.relaxed.gpu.global.u32 %0, [%1];" : "=r"(v) : "l"(p) : "memory");
  return v;
}
__device__ __forceinline__ void st_relaxed(uint32_t* p, uint32_t v) {
  asm volatile("st.relaxed.gpu.global.u32 [%0], %1;" ::"l"(p), "r"(v) : "memory");
}
__device__ __forceinline__ uint4 ld_ll(const void* p) {
  uint4 v;
  asm volatile("{\n.reg .b128 t;\n.reg .b64 lo, hi;\nld.relaxed.gpu.global.b128 t, [%4];\nmov.b128 {lo, hi}, t;\n"
               "mov.b64 {%0,%1}, lo;\nmov.b64 {%2,%3}, hi;\n}" : "=r"(v.x), "=r"(v.y), "=r"(v.z), "=r"(v.w) : "l"(p) : "memory");
  return v;
}
__device__ __forceinline__ void st_ll(void* p, uint32_t x, uint32_t y, uint32_t z, uint32_t w) {
  asm volatile("{\n.reg .b128 t;\n.reg .b64 lo, hi;\nmov.b64 lo, {%0,%1};\nmov.b64 hi, {%2,%3};\nmov.b128 t, {lo, hi};\n"
               "st.relaxed.gpu.global.b128 [%4], t;\n}" ::"r"(x), "r"(y), "r"(z), "r"(w), "l"(p) : "memory");
}
__device__ __forceinline__ void st_ll_if(bool on, void* p, uint32_t x, uint32_t y, uint32_t z, uint32_t w) {
  asm volatile("{\n.reg .pred p;\nsetp.ne.u32 p, %5, 0;\n@p st.relaxed.gpu.global.v4.u32 [%4], {%0,%1,%2,%3};\n}"
               ::"r"(x), "r"(y), "r"(z), "r"(w), "l"(p), "r"((uint32_t)on) : "memory");
}
__device__ __forceinline__ uint32_t sel(bool c, uint32_t a, uint32_t b) {
  uint32_t r;
  asm("{\n.reg .pred p;\nsetp.ne.u32 p, %3, 0;\nselp.b32 %0, %1, %2, p;\n}" : "=r"(r) : "r"(a), "r"(b), "r"((uint32_t)c));
  return r;
}
__device__ __forceinline__ float self(bool c, float a, float b) { return __uint_as_float(sel(c, __float_as_uint(a), __float_as_uint(b))); }
__device__ __forceinline__ float4 lds128(uint32_t a) {
  float4 v;
  asm volatile("ld.shared.v4.f32 {%0,%1,%2,%3}, [%4];" : "=f"(v.x), "=f"(v.y), "=f"(v.z), "=f"(v.w) : "r"(a) : "memory");
  return v;
}
template <int I> struct Idx { static constexpr int v = I; };
template <int B, int E, class F> __device__ __forceinline__ void static_for(F f) {
  if constexpr (B < E) { f(Idx<B>()); static_for<B + 1, E>(f); }
}
template <int OFFSET> __device__ __forceinline__ uint4 lds128i(uint32_t a) {
  uint4 v;
  asm volatile("ld.shared.v4.u32 {%0,%1,%2,%3}, [%4+%5];" : "=r"(v.x), "=r"(v.y), "=r"(v.z), "=r"(v.w) : "r"(a), "n"(OFFSET) : "memory");
  return v;
}
__device__ __forceinline__ uint32_t tag_lo(uint32_t v, uint32_t tag_hi) { return __byte_perm(v, tag_hi, 0x7610); }
__device__ __forceinline__ uint32_t tag_up(uint32_t v, uint32_t tag_hi) { return __byte_perm(v, tag_hi, 0x7632); }
__device__ __forceinline__ uint32_t untag(uint32_t a, uint32_t b) { return __byte_perm(a, b, 0x5410); }
__device__ __forceinline__ void stsm4(uint32_t a, uint32_t r0, uint32_t r1, uint32_t r2, uint32_t r3) {
  asm volatile("stmatrix.sync.aligned.m8n8.x4.shared.b16 [%0], {%1,%2,%3,%4};" ::"r"(a), "r"(r0), "r"(r1), "r"(r2), "r"(r3) : "memory");
}
__device__ __forceinline__ void ldsm4(uint32_t a, uint32_t* r) {
  asm volatile("ldmatrix.sync.aligned.m8n8.x4.shared.b16 {%0,%1,%2,%3}, [%4];" : "=r"(r[0]), "=r"(r[1]), "=r"(r[2]), "=r"(r[3]) : "r"(a) : "memory");
}
__device__ __forceinline__ void ldsm4t(uint32_t a, uint32_t* r) {
  asm volatile("ldmatrix.sync.aligned.m8n8.x4.trans.shared.b16 {%0,%1,%2,%3}, [%4];" : "=r"(r[0]), "=r"(r[1]), "=r"(r[2]), "=r"(r[3]) : "r"(a) : "memory");
}
__device__ __forceinline__ void mma16816(float* c, uint32_t a0, uint32_t a1, uint32_t a2, uint32_t a3, uint32_t b0, uint32_t b1) {
  asm("mma.sync.aligned.m16n8k16.row.col.f32.bf16.bf16.f32 {%0,%1,%2,%3}, {%4,%5,%6,%7}, {%8,%9}, {%0,%1,%2,%3};"
      : "+f"(c[0]), "+f"(c[1]), "+f"(c[2]), "+f"(c[3]) : "r"(a0), "r"(a1), "r"(a2), "r"(a3), "r"(b0), "r"(b1));
}
__device__ __forceinline__ void mma1688(float* c, uint32_t a0, uint32_t a1, uint32_t b0) {
  asm("mma.sync.aligned.m16n8k8.row.col.f32.bf16.bf16.f32 {%0,%1,%2,%3}, {%4,%5}, {%6}, {%0,%1,%2,%3};"
      : "+f"(c[0]), "+f"(c[1]), "+f"(c[2]), "+f"(c[3]) : "r"(a0), "r"(a1), "r"(b0));
}
__device__ __forceinline__ uint32_t pack(float lo, float hi) {
  uint32_t r;
  asm("cvt.rn.bf16x2.f32 %0, %1, %2;" : "=r"(r) : "f"(hi), "f"(lo));
  return r;
}
__device__ __forceinline__ float lo_f(uint32_t v) { return __uint_as_float(v << 16); }
__device__ __forceinline__ float hi_f(uint32_t v) { return __uint_as_float(v & 0xffff0000u); }
__device__ __forceinline__ float rbf(float v) { return hi_f(pack(0.f, v)); }
__device__ __forceinline__ uint32_t sub_bf2(uint32_t a, uint32_t b) {
  uint32_t r;
  asm("sub.rn.bf16x2 %0, %1, %2;" : "=r"(r) : "r"(a), "r"(b));
  return r;
}
__device__ __forceinline__ uint32_t mul_bf2(uint32_t a, uint32_t b) {
  uint32_t r;
  asm("mul.rn.bf16x2 %0, %1, %2;" : "=r"(r) : "r"(a), "r"(b));
  return r;
}
__device__ __forceinline__ uint32_t add_bf2(uint32_t a, uint32_t b) {
  uint32_t r;
  asm("add.rn.bf16x2 %0, %1, %2;" : "=r"(r) : "r"(a), "r"(b));
  return r;
}
__device__ __forceinline__ float ex2(float x) {
  float r;
  asm("ex2.approx.ftz.f32 %0, %1;" : "=f"(r) : "f"(x));
  return r;
}
__device__ __forceinline__ float shfl_x(float v, int m) { return __shfl_xor_sync(0xffffffffu, v, m); }
template <int N> __device__ __forceinline__ void acc_max(const float* s, float& m0, float& m1, float& m2, float& m3) {
#pragma unroll
  for (int i = 0; i < N; i += 8) {
    m0 = fmaxf(m0, fmaxf(s[i], s[i + 1])); m1 = fmaxf(m1, fmaxf(s[i + 2], s[i + 3]));
    m2 = fmaxf(m2, fmaxf(s[i + 4], s[i + 5])); m3 = fmaxf(m3, fmaxf(s[i + 6], s[i + 7]));
  }
}
__device__ __forceinline__ float fmin_nan(float a, float b) { float r; asm("min.NaN.f32 %0, %1, %2;" : "=f"(r) : "f"(a), "f"(b)); return r; }
__device__ __forceinline__ float fmax_nan(float a, float b) { float r; asm("max.NaN.f32 %0, %1, %2;" : "=f"(r) : "f"(a), "f"(b)); return r; }
__device__ __forceinline__ float rcp(float x) {
  float r;
  asm("rcp.approx.ftz.f32 %0, %1;" : "=f"(r) : "f"(x));
  return r;
}
__device__ __forceinline__ uint32_t to_key(float f, uint32_t inv_tok2) {
  const uint32_t u = __float_as_uint(f);
  return (f == f ? (u ^ ((uint32_t)((int)u >> 31) | 0x80000000u)) & 0xfffff000u : 0x1000u) | inv_tok2;
}
__device__ __forceinline__ float key_score(uint32_t k) { return __uint_as_float(k ^ ((uint32_t)((int)~k >> 31) | 0x80000000u)); }
__device__ __forceinline__ uint32_t key_token(uint32_t k) { return (~k >> 1) & 2047u; }
__device__ __forceinline__ uint32_t key_cand(uint32_t k) { return (key_token(k) >> 4) * 2 + (k & 1); }
__device__ __forceinline__ void top2(uint32_t key, uint32_t& k1, uint32_t& k2) {
  k1 = __reduce_max_sync(0xffffffffu, key);
  k2 = __reduce_max_sync(0xffffffffu, key == k1 ? 0u : key);
}
__device__ __forceinline__ uint32_t keep(uint32_t v) { return __shfl_sync(0xffffffffu, v, threadIdx.x & 31); }
#define OFF(member) ((uint32_t)((const char*)&((Scratch*)0)->member - (const char*)0))

#define TSC(a, b)
#define TSH(a, b, c)
#define TSA(a, b, c)
#define TSB(a, b)
#define TS(slot, i)
#define TSL(slot, i)
#define TSV(slot, i, v)
#define TSDUMP()

__global__ void __launch_bounds__(NTHREADS, 1)
fused_block_kernel(const Params P, const __grid_constant__ CUtensorMap tm_x, const __grid_constant__ CUtensorMap tm_w,
                   const __grid_constant__ CUtensorMap tm_wo,
                   const __grid_constant__ CUtensorMap tm_d, const __grid_constant__ CUtensorMap tm_g, const __grid_constant__ CUtensorMap tm_u) {
  extern __shared__ __align__(1024) unsigned char smem[];
  const uint32_t sb = (uint32_t)__cvta_generic_to_shared(smem);
  const int tid = threadIdx.x, lane = tid & 31;
  const int warp = __shfl_sync(0xffffffffu, tid >> 5, 0);
  const int cta = blockIdx.x, m = (cta >> 4) * 2 + (cta & 1), g = (cta >> 1) & 7;
  const int col0 = (56 * g) & ~15;
  const int q = lane & 3, r8 = lane >> 2;
  Scratch* const sc = P.sc;
  auto bar = [&](int i) { return sb + R_BAR + 8 * i; };

  if (warp == 0 && elect()) {
#pragma unroll
    for (int i = B_X; i < B_W; i++) mbar_init(bar(i), 1);
    asm volatile("fence.mbarrier_init.release.cluster;" ::: "memory");
#pragma unroll 1
    for (int c = 0; c < 7; c++) {
      mbar_expect(bar(B_X + c), 16384);
      tma2d(sb + x_off(c), &tm_x, 64 * c, 128 * m, bar(B_X + c));
    }
  }
  if (warp >= 8) {
    asm volatile("setmaxnreg.dec.sync.aligned.u32 40;");
    const int j = warp - 8;
    if (j == 1 && elect()) {
      asm volatile("prefetch.tensormap [%0];" ::"l"(&tm_w) : "memory");
#pragma unroll
      for (int i = B_W; i < B_COUNT; i++) mbar_init(bar(i), bar_count(i));
      asm volatile("fence.mbarrier_init.release.cluster;" ::: "memory");
    }
    const uint32_t epoch = ld_relaxed(&sc->epoch[0]) + 1;
    bar_sync(0, NTHREADS);
    if (j == 0) {
      if (elect()) {
        auto publish = [&](int kv, int w) {
          fence_async_smem();
          bulk_store(&sc->kv[2 * m + w][g][kv][0][0], sb + own_off(kv, 0) + w * 4096, 4096);
          bulk_store(&sc->kv[2 * m + w][g][kv][1][0], sb + own_off(kv, 1) + w * 4096, 4096);
        };
#pragma unroll 1
        for (int c = 0; c < 12; c++) {
          if (c == 8) mbar_wait_tma(bar(B_XC));
          if (c >= 10) {
            mbar_wait_tma(bar(B_KD0 + c - 10));
            publish(0, c - 10);
          }
          mbar_expect(bar(B_W + c), 14336);
          tma2d(sb + sec_off(c >> 2) + 14336 * (c & 3), &tm_w, col0 + (c >= 8 ? 0 : 448 + 448 * (c >> 2)), 112 * (c & 3), bar(B_W + c));
          if (c == 7) TSL(2, 0);
        }
#pragma unroll 1
        for (int w = 0; w < 2; w++) { mbar_wait_tma(bar(B_VD0 + w)); publish(1, w); }
        asm volatile("cp.async.bulk.commit_group;" ::: "memory");
        TSL(2, 10);
        mbar_wait_tma(bar(B_QD0)); mbar_wait_tma(bar(B_QD1));
        mbar_wait(bar(B_VL + 1));
        mbar_expect(bar(B_WO), 49152);
        tma3d(sb + R_Q, &tm_wo, col0, 0, bar(B_WO)); tma3d(sb + R_Q + 24576, &tm_wo, col0, 32, bar(B_WO));
        mbar_expect(bar(B_XS), 16384);
        tma2d(sb + X_SL, &tm_x, col0, 128 * m, bar(B_XS));
        if (cta < NFFN) {
          mbar_expect(bar(B_FF), FTMA ? 43008 : 14336);
          tma3d(sb + R_F + 28672, &tm_d, 0, 16 * cta, bar(B_FF));
          if (FTMA) {
#pragma unroll 1
            for (int i = 0; i < 4; i++) {
              if (i == FTMA - 1) { mbar_wait(bar(B_OS0)); mbar_wait(bar(B_OS1)); }
              tma2d(sb + R_F + 7168 * i, i & 2 ? &tm_u : &tm_g, 16 * cta, 224 * (i & 1), bar(B_FF));
            }
            mbar_arrive(bar(B_FF));
          }
        }
        asm volatile("cp.async.bulk.wait_group.read 0;" ::: "memory");
      }
    } else {
      const uint32_t tag = (epoch & 127) << 16;
      if (j == 3) {
        mbar_wait_tma(bar(B_X + 6));
        if (cta < NFFN && lane < 28) {
          const char* wrow = (const char*)P.wqkv + (4 * cta + lane / 7) * 2688 + (lane % 7) * 128;
          asm volatile("prefetch.global.L2 [%0];" ::"l"(wrow + 1792));
          asm volatile("prefetch.global.L2 [%0];" ::"l"(wrow));
          asm volatile("prefetch.global.L2 [%0];" ::"l"((const char*)P.wo + cta * 3584 + lane * 128));
        }
        float ws = 0.f;
#pragma unroll
        for (int i = 0; i < 7; i++) { const uint32_t v = __ldg((const uint32_t*)P.wr + 32 * i + lane); ws += lo_f(v) + hi_f(v); }
        const uint32_t own = __ldg((const uint32_t*)P.wr + 28 * g + min(lane, 27));
#pragma unroll
        for (int i = 1; i < 32; i <<= 1) ws += shfl_x(ws, i);
        ((uint32_t*)(smem + R_WR))[lane] = lane < 28 ? own : __float_as_uint(ws);
        __syncwarp();
        if (lane == 0) mbar_arrive(bar(B_XS));
#pragma unroll 1
        for (int a = 0; a < 3; a++) {
          mbar_wait_tma(bar(B_W + 1 + 2 * a));
          const char* p = (const char*)(a == 0 ? P.wg : (a == 1 ? P.wu : P.wd)) + cta * 12544 + lane * 128;
          asm volatile("prefetch.global.L2 [%0];\nprefetch.global.L2 [%0+4096];\nprefetch.global.L2 [%0+8192];" ::"l"(p));
          if (lane < 2) asm volatile("prefetch.global.L2 [%0+12288];" ::"l"(p));
        }
      }
      if (j < 3) {
        const int hh = j - 1, first = max(4 - 2 * m, 0), kv = (lane >> 2) & 1;
        const uint4* src = &sc->kv[2 * m - 4 + max(q, first)][g][kv][hh][0];
        const uint32_t toff = lane * 128 + (q ^ 3) * 16 + 8 - 8 * hh;
        const uint32_t dk = rem_off(0, hh), dv = rem_off(1, hh);
        if (first) {
          mbar_wait(bar(B_KD1));
#pragma unroll 1
          for (int i = 0; i < 2 * first; i++) *(uint32_t*)(smem + dk + toff + (i >> 1) * 4096 + (i & 1) * 64) = 0xff80u;
          fence_async_smem();
          __syncwarp();
        }
        int spins = 0;
        uint32_t bad, tries = 0, is_free = 0, lb = bar(B_KL + 2 * kv + hh);
#pragma unroll 1
        do {
          if (tries ? lane == 0 : (lane & 27) == 0) mbar_expect(lb, (4 - first) * (tries ? 8192 : 4096));
          uint32_t todo = ((15u << first) & 15u) * 17u;
#pragma unroll 1
          while (todo && ++spins < SPIN_LIMIT) {
            const uint32_t now = todo & is_free & __ballot_sync(0xffffffffu, (ld_relaxed((const uint32_t*)src + 1010 - 2 * hh) ^ tag) <= 0xffffu);
            if ((now >> lane) & 1) bulk_load(sb + (kv ? dv : dk) + q * 4096, src, 4096, lb);
            todo &= ~now;
            if (is_free != 255u && mbar_test(bar(is_free ? B_VD1 : B_KD1))) is_free = is_free * 16 + 15;
          }
          if (lane == 0 && hh == 0) TSL(2, 6);
          if (tries) mbar_wait(lb, (tries - 1) & 1);
          else { mbar_wait(bar(B_KL + hh)); mbar_wait(bar(B_VL + hh)); }
          if (lane == 0) TSL(2, 8 + hh);
          lb = bar(B_KR + hh);
          tries++;
          bad = 0;
#pragma unroll 2
          for (int i = first; i < 4; i++) {
            const volatile uint32_t* pk_ = (const volatile uint32_t*)(smem + dk + toff + i * 4096);
            const volatile uint32_t* pv_ = (const volatile uint32_t*)(smem + dv + toff + i * 4096);
            bad |= ((pk_[0] ^ tag) | (pk_[16] ^ tag)) | ((pv_[0] ^ tag) | (pv_[16] ^ tag));
          }
        } while (__any_sync(0xffffffffu, bad > 0xffffu) && ++spins < SPIN_LIMIT);
        if (lane == 0) { ((uint32_t*)(smem + R_WR))[32 + hh] = tries - 1; mbar_arrive(bar(B_KVF)); TSL(2, 1 + hh); }
      } else {
        mbar_wait(bar(B_VL + 1)); mbar_wait_tma(bar(B_VD1));
        const int row = lane >> 3;
        const char* src = (const char*)P.wo + col0 * 2 + (lane & 7) * 16 + ((row & 1) ? 8 + row : 24 + (row >> 1)) * 896;
        const int step4 = ((row & 1) ? 4 : 2) * 896, step_h = ((row & 1) ? 32 : 4) * 896 - 8 * 50176;
        uint32_t dst = sb + R_M0 + row * 128 + ((lane ^ row) & 7) * 16;
#pragma unroll 1
        for (int i = 0; i < 16; i++) {
          if (i == 8) { src += step_h; dst += R_M1 - R_M0 - 8192; }
          asm volatile("cp.async.cg.shared.global [%0], [%1], 16;" ::"r"(dst), "l"(src) : "memory");
          asm volatile("cp.async.cg.shared.global [%0], [%1], 16;" ::"r"((dst ^ 64) + 512), "l"(src + step4) : "memory");
          src += 50176; dst += 1024;
        }
        asm volatile("cp.async.wait_all;" ::: "memory");
        fence_async_smem();
        __syncwarp();
        if (lane == 0) mbar_arrive(bar(B_WO));
      }
    }
    __syncwarp();
    if (j >= 2) {
      const int w = j - 2;
      const uint4* src = &sc->o[0][2 * m + w][0][0][0][0];
      const uint32_t tag = (epoch & 127) << 16;
      int spins = 0;
      mbar_wait(bar(B_U0));
#pragma unroll 1
      while (__any_sync(0xffffffffu, (ld_relaxed(&src[64 * min(lane, 23) + 63].x) ^ tag) > 0xffffu) && ++spins < SPIN_LIMIT) {}
      if (elect()) {
        mbar_expect(bar(B_OS0 + w), 24576);
        bulk_load(sb + (w ? 40960 : R_V), src, 16384, bar(B_OS0 + w));
        bulk_load(sb + (w ? 57344 : 32768), src + 1024, 8192, bar(B_OS0 + w));
      }
      if (lane == 0) TSL(2, 12 + w);
    }
    if (!FTMA && j == 1 && cta < NFFN) {
      mbar_wait(bar(B_VL + 1));
      const uint32_t row = lane >> 1, dst = sb + R_F + row * 32 + ((lane ^ (lane >> 3)) & 1) * 16;
      const size_t off = (size_t)row * 3584 + cta * 32 + (lane & 1) * 16;
#pragma unroll 1
      for (int i = 0; i < 28; i++) {
        if (i == 6) { mbar_wait(bar(B_OS0)); mbar_wait(bar(B_OS1)); }
        asm volatile("cp.async.cg.shared.global [%0], [%1], 16;" ::"r"(dst + 512 * i), "l"((const char*)P.wg + off + 57344 * i) : "memory");
        asm volatile("cp.async.cg.shared.global [%0], [%1], 16;" ::"r"(dst + 14336 + 512 * i), "l"((const char*)P.wu + off + 57344 * i) : "memory");
      }
      asm volatile("cp.async.wait_all;" ::: "memory");
      __syncwarp();
      if (lane == 0) { mbar_arrive(bar(B_FF)); TSL(2, 3); }
    }
    if (j == 1) {
      const uint32_t tag_hi = epoch << 16;
      const int tk = (lane >> 1) & 1, n = 16 * (cta >> 2) + 2 * (cta & 3) + (lane & 1) + 2 * (lane & 4), nc = n % 56;
      const uint32_t o_fp = keep(OFF(crow[0][0][min(n / 56, 7)][((nc > 31 || (nc > 23 && (nc & 1))) ? 4 : 0) + ((nc & 7) >> 1)]));
      const uint4* rp = &sc->rec[g][lane];
      uint4 u[4];
      int spins = 0;
      mbar_wait(bar(B_S1));
#pragma unroll 1
      do {
#pragma unroll
        for (int i = 0; i < 4; i++) u[i] = ld_ll(rp + 32 * i);
      } while (__any_sync(0xffffffffu, (((u[0].w ^ epoch) | (u[1].w ^ epoch)) | ((u[2].w ^ epoch) | (u[3].w ^ epoch))) != 0) && ++spins < SPIN_LIMIT);
      if (lane == 0) TSL(2, 14);
      const uint32_t rk1 = __reduce_max_sync(0xffffffffu, max(max(u[0].x, u[1].x), max(u[2].x, u[3].x)));
      uint32_t rk2 = 0;
#pragma unroll
      for (int i = 0; i < 4; i++) rk2 = max(rk2, u[i].x == rk1 ? u[i].y : u[i].x);
      rk2 = __reduce_max_sync(0xffffffffu, rk2);
      const uint32_t c1 = key_cand(rk1), c2 = key_cand(rk2);
      const uint32_t o1 = OFF(crow[0][0][0][lane]) + c1 * 2048, o2 = OFF(crow[0][0][0][lane]) + c2 * 2048;
      uint4 t[4], fa, fb;
#pragma unroll 1
      do {
        t[0] = ld_ll((const char*)sc + o1); t[1] = ld_ll((const char*)sc + o1 + 512); t[2] = ld_ll((const char*)sc + o2); t[3] = ld_ll((const char*)sc + o2 + 512);
      } while (__any_sync(0xffffffffu, (((t[0].w ^ tag_hi) | (t[1].w ^ tag_hi)) | ((t[2].w ^ tag_hi) | (t[3].w ^ tag_hi))) > 0xffffu) && ++spins < SPIN_LIMIT);
#pragma unroll
      for (int i = 0; i < 4; i++) *(uint4*)(smem + SMALL + 4096 + 512 * i + 16 * lane) = t[i];
      if (lane == 0) *(uint2*)(smem + R_WR + 136) = make_uint2(key_token(rk1), key_token(rk2));
      __syncwarp();
      if (lane == 0) { mbar_arrive(bar(B_ROW)); TSL(2, 15); }
      const char* fp = (const char*)sc + o_fp + key_cand(tk ? rk2 : rk1) * 2048;
#pragma unroll 1
      do { fa = ld_ll(fp); fb = ld_ll(fp + 1024); }
      while (__any_sync(0xffffffffu, ((fa.w ^ tag_hi) | (fb.w ^ tag_hi)) > 0xffffu) && ++spins < SPIN_LIMIT);
      const uint32_t ua = (nc & 16) ? ((nc & 8) ? fa.w : fa.z) : ((nc & 8) ? fa.y : fa.x);
      const uint32_t ub = (nc & 16) ? ((nc & 8) ? fb.w : fb.z) : ((nc & 8) ? fb.y : fb.x);
      const bool hi = (nc & 1) && (nc >> 3) != 3;
      if (lane < 8)
        *(uint4*)(smem + SMALL + 2048 + 16 * lane) = make_uint4(hi ? ua & 0xffff0000u : ua << 16, hi ? ub & 0xffff0000u : ub << 16,
            __float_as_uint(rbf(rcp(1.f + ex2(-1.4426950408889634f * rbf(key_score(tk ? rk2 : rk1)))))), key_token(tk ? rk2 : rk1) * D_ + n);
      __syncwarp();
      if (lane == 0) mbar_arrive(bar(B_FIN));
    }
    mbar_wait(bar(B_WIN)); mbar_wait(bar(B_ROW));
    const uint2 win = *(const uint2*)(smem + R_WR + 136);
    char* const op = (char*)P.out + (128 * m + 32 * j) * 896 + 112 * g;
#pragma unroll 1
    for (int i = 0; i < 7; i++) {
      const int id = lane + 32 * i, r = (id * 9363) >> 16;
      const uint4 v = *(const uint4*)(smem + X_SL + 4096 * j + 16 * id + (r >> 4) * 256);
      const uint32_t tok = 128 * m + 32 * j + r;
      if (tok != win.x && tok != win.y) *(uint4*)(op + r * 784 + 16 * id) = v;
    }
    return;
  }

  asm volatile("setmaxnreg.inc.sync.aligned.u32 232;");
  const int w = warp >> 2, wi = warp & 3;
  const bool bsel = r8 & 1;
  const int tile = 8 * m + warp, row0 = 16 * tile;
  const int dsrc = (lane & 28) | (r8 >> 1);
  const uint32_t frag_off = (16 * warp + (lane & 15)) * 128 + ((lane >> 4) ^ (lane & 7)) * 16;
  const uint32_t kv_frag = sb + (16 * warp + (lane & 15)) * 64 + ((lane >> 4) ^ ((lane >> 1) & 3)) * 16;
  uint32_t A[112];
  const uint32_t epoch = ld_relaxed(&sc->epoch[0]) + 1, tag_hi = epoch << 16;
  float rstd0, rstd1;
  uint32_t mb[2];
  const uint32_t otag = keep((epoch & 127) << 16);
  char* const scb = (char*)sc;
  auto clear_slots = [&]() {
    const uint32_t e = epoch - 1;
    const char* po = (const char*)&sc->o[(lane >> 3) & 1][2 * m][g][wi][1][lane | 24];
    const char* ps = (const char*)&sc->stats[8 * m + wi][g][lane & 15];
    const char* pr = (const char*)&sc->rec[g][8 * m + wi];
    const char* pp = (const char*)&sc->part[16 * wi + 4 * q + (r8 >> 1)][cta][r8 & 1];
#pragma unroll
    for (int ww = 0; ww < 2; ww++) {
      st_ll_if(lane >= 16, (void*)(po + 32768 * ww), (e & 127) << 16, 0, 0, 0);
      st_ll_if(lane < 16, (void*)(ps + 8192 * ww), 0, 0, 0, e);
      st_ll_if(lane == 0, (void*)(pr + 64 * ww), 0, 0, 0, e);
      st_ll_if(cta < NFFN && (ww == 0 || wi < 3), (void*)(pp + 229376 * ww), 0, 0, 0, e);
    }
  };
  const int dg = 16 * wi + r8 - 2 * q;
  uint32_t mk[9];
#pragma unroll
  for (int i = 0; i < 9; i++) mk[i] = keep(__funnelshift_lc(0xffffffffu, 0u, __viaddmax_s32(16 * dg, 144 - 128 * i, 0)));
  const int rloc = r8 + 4 * (q & 2);
  bar_sync(0, NTHREADS);
  TS(w, 0);
  {
    float c0[4] = {0.f, 0.f, 0.f, 0.f}, c1[4] = {0.f, 0.f, 0.f, 0.f}, c2[4] = {0.f, 0.f, 0.f, 0.f}, c3[4] = {0.f, 0.f, 0.f, 0.f}, c4[4] = {0.f, 0.f, 0.f, 0.f}, c5[4] = {0.f, 0.f, 0.f, 0.f};
    const uint32_t xa = sb + frag_off;
#pragma unroll
    for (int L = 0; L < 7; L++) {
      mbar_wait_tma(bar(B_X + L));
      if (L == 0) TS(w, 28);
      if (L == 6) TS(w, 29);
#pragma unroll
      for (int t = 0; t < 4; t++) ldsm4((xa ^ (32 * t)) + x_off(L), A + 16 * L + 4 * t);
#pragma unroll
      for (int t = 0; t < 4; t++) {
        const uint32_t* a = A + 16 * L + 4 * t;
        mma16816((t & 1) ? c5 : c0, a[0], a[1], a[2], a[3], 0x3f803f80u, 0x3f803f80u);
        mma1688(c1, a[0], a[1], a[0]); mma1688(c2, a[0], a[1], a[1]);
        mma1688(c3, a[2], a[3], a[2]); mma1688(c4, a[2], a[3], a[3]);
      }
    }
    const float mu0 = (c0[0] + c5[0]) * (1.f / D_), mu1 = (c0[2] + c5[2]) * (1.f / D_);
    mb[0] = pack(mu0, mu0); mb[1] = pack(mu1, mu1);
    pin<2>(mb);
    __syncwarp();
    if (lane == 0) mbar_arrive(bar(B_XC));
    if (w) clear_slots();
    if (w) { mbar_wait_tma(bar(B_CN)); mb[0] = keep(mb[0]); mb[1] = keep(mb[1]); }
#pragma unroll
    for (int i = 0; i < 112; i++) A[i] = sub_bf2(A[i], mb[i & 1]);
    const float q0 = __shfl_sync(0xffffffffu, bsel ? c1[1] + c3[1] : c1[0] + c3[0], dsrc);
    const float q1 = __shfl_sync(0xffffffffu, bsel ? c2[3] + c4[3] : c2[2] + c4[2], dsrc);
    rstd0 = rsqrtf(fmaxf(fmaf(q0, 1.f / D_, -mu0 * mu0), 0.f) + 1e-5f);
    rstd1 = rsqrtf(fmaxf(fmaf(q1, 1.f / D_, -mu1 * mu1), 0.f) + 1e-5f);
    if (!w) { pin<112>(A); mbar_arrive_if(lane == 0, bar(B_CN) + (keep(A[111]) & 0)); }
    TS(w, 1);
  }

  uint32_t pk[14], t0[2], t1[2];
  {
    float acc[28];
#pragma unroll
    for (int i = 0; i < 28; i++) acc[i] = 0.f;
#pragma unroll 1
    for (int p = 0; p < 3; p++) {
      if (p + w > 0) bar_sync(1 + w, 256);
      const uint64_t db = mkdesc(sb + sec_off(p) + (g & 1) * 16);
      pin<28>(acc);
#pragma unroll
      for (int c = 0; c < 4; c++) {
        mbar_wait_tma(bar(B_W + 4 * p + c));
        pin<28>(A + 28 * c);
        wg_fence();
#pragma unroll
        for (int t = 7 * c; t < 7 * c + 7; t++) wg_n56_t(acc, A[4 * t], A[4 * t + 1], A[4 * t + 2], A[4 * t + 3], db + t * 128, t > 0);
        wg_commit();
      }
      if (p + w < 3) bar_arrive(2 - w, 256);
      TSA(w, 2 + 3 * p, 2);
      wg_wait0();
      pin<28>(acc);
      TSA(w, 3 + 3 * p, 3);
      const float qs = p == 2 ? 0.18898223650461362f * 1.4426950408889634f : 1.f;
      const float f0 = rstd0 * qs, f1 = rstd1 * qs;
      const uint32_t padv = sel(p == 2, 0x3f803f80u, otag | (p * 0x3f80u));
#pragma unroll
      for (int j = 0; j < 7; j++) {
        pk[j] = pack(acc[4 * j] * f0, acc[4 * j + 1] * f0);
        pk[7 + j] = pack(acc[4 * j + 2] * f1, acc[4 * j + 3] * f1);
      }
#pragma unroll
      for (int h = 0; h < 2; h++) { t0[h] = sel(q < 2, pk[7 * h + 3], padv); t1[h] = sel(q < 2, padv, pk[7 * h + 3]); }
      if (p < 2) {
        mbar_wait_tma(bar(p ? B_KD1 : B_XC));
        const uint32_t b0 = kv_frag + own_off(p, 0), b1 = kv_frag + own_off(p, 1);
        stsm4(b0, pk[0], pk[7], pk[1], pk[8]);   stsm4(b0 ^ 32, pk[2], pk[9], t0[0], t0[1]);
        stsm4(b1, pk[4], pk[11], pk[5], pk[12]); stsm4(b1 ^ 32, pk[6], pk[13], t1[0], t1[1]);
      } else {
        fence_async_smem();
      }
      __syncwarp();
      if (lane == 0) mbar_arrive(bar(B_KD0 + 2 * p + w));
      TSA(w, 4 + 3 * p, 4);
    }
  }
  float hv[28];
  uint32_t o_so, o_si, o_cp, inv_tok;
  uint32_t xs[16], bw[7], a_ci, o_rp, o_pp, o_gp, f1w, f1r, a_wa, a_wb, a_st;
  float wsum;
  {
    const uint4* const ip = (const uint4*)(scb + keep(OFF(o[0][2 * m + w][0][wi][0][lane])));
    uint4* const op = (uint4*)ip + 256 * g;
    {
      uint32_t qa[8] = {pk[0], pk[7], pk[1], pk[8], pk[2], pk[9], t0[0], t0[1]};
      uint32_t qb[8] = {pk[4], pk[11], pk[5], pk[12], pk[6], pk[13], t1[0], t1[1]};
      const uint64_t d0 = mkdesc64(sb), dw = d0 + w * 256;
      mbar_wait(bar(B_KL));
      TS(w, 11);
      float s[128], sd[32], o[16];
      uint32_t pp[80];
      auto scores_a = [&](const uint32_t* qq, int hh) {
        const uint64_t df = dw + rem_off(0, hh) / 16, dd = dw + own_off(0, hh) / 16;
        wg_fence();
        wg_n64(s, qq[0], qq[1], qq[2], qq[3], df, 0);
        wg_n64(s, qq[4], qq[5], qq[6], qq[7], df + 2, 1);
        wg_n64(sd, qq[0], qq[1], qq[2], qq[3], dd, 0);
        wg_n64(sd, qq[4], qq[5], qq[6], qq[7], dd + 2, 1);
        wg_commit();
      };
      auto scores_b = [&](const uint32_t* qq, int hh) {
        const uint64_t d = dw + rem_off(0, hh) / 16 + 256, d3 = d0 + (w ? own_off(0, hh) : rem_off(0, hh) + 12288) / 16;
        wg_fence();
        wg_n128(s + 32, qq[0], qq[1], qq[2], qq[3], d, 0);
        wg_n128(s + 32, qq[4], qq[5], qq[6], qq[7], d + 2, 1);
        wg_n64(s + 96, qq[0], qq[1], qq[2], qq[3], d3, 0);
        wg_n64(s + 96, qq[4], qq[5], qq[6], qq[7], d3 + 2, 1);
        wg_commit();
        wg_wait1();
        pin<32>(s); pin<32>(sd);
#pragma unroll
        for (int i = 0; i < 32; i++) sd[i] = (8 * ((i >> 2) - ((i >> 1) & 1)) + (i & 1) <= dg) ? sd[i] : s[i];
        pin<32>(sd);
      };
      uint32_t reload = 0;
      auto softmax_pv = [&](int hh, bool shift, float m0, float m1, bool hand) {
        auto expo = [&](int lo, int hi) {
#pragma unroll
          for (int i = lo; i < hi; i++) {
            const float* sp = i < 16 ? sd : s;
            const float mm = (i & 1) ? m1 : m0;
            pp[i] = shift ? pack(ex2(sp[2 * i] - mm), ex2(sp[2 * i + 1] - mm)) : pack(ex2(sp[2 * i]), ex2(sp[2 * i + 1]));
          }
          pin<16>(pp + hi - 16);
        };
        auto pv = [&](const uint32_t* p, uint64_t d, bool first) {
#pragma unroll
          for (int k = 0; k < 4; k++) wg_n32_t(o, p[4 * k], p[4 * k + 1], p[4 * k + 2], p[4 * k + 3], d + k * 64, !first || k > 0);
        };
        expo(0, 32);
#pragma unroll
        for (int i = 0; i < 16; i++) {
          const uint32_t k = mk[(i >> 1) - (i & 1) + 1];
          pp[64 + i] = pp[i] & k;
          pp[i] &= ~k;
        }
        pin<16>(pp); pin<16>(pp + 64);
        const uint64_t dv = dw + rem_off(1, hh) / 16;
        const bool late_v = !shift && hh == 0;
        mbar_wait(bar(B_KL));
        mbar_arrive_if(hand && lane == 0, bar(B_E + 2 * hh + w));
        if (!late_v) {
          wg_fence();
          pv(pp + 64, dw + own_off(1, hh) / 16, true); pv(pp, dv, false);
          wg_commit();
        }
        expo(32, 48);
        if (late_v) mbar_wait(bar(B_VL));
        wg_fence();
        if (late_v) { pv(pp + 64, dw + own_off(1, hh) / 16, true); pv(pp, dv, false); }
        pv(pp + 16, dv + 256, false);
        wg_commit();
        expo(48, 64);
        TSH(w, 14 + 4 * hh, 14);
        wg_fence();
        pv(pp + 32, dv + 512, false); pv(pp + 48, d0 + (w ? own_off(1, hh) : rem_off(1, hh) + 12288) / 16, false);
        wg_commit();
        if (!shift && hh == 0) {
          mbar_wait(bar(B_KVF));
          reload = ((const volatile uint32_t*)(smem + R_WR))[32] | ((const volatile uint32_t*)(smem + R_WR))[33];
        }
        wg_wait0();
        pin<16>(o);
      };
      auto finish = [&](int hh, bool check, uint32_t reloaded) {
        const int lsrc = (lane & 28) | (2 - 2 * hh);
        const float sum0 = __shfl_sync(0xffffffffu, o[12], lsrc), sum1 = __shfl_sync(0xffffffffu, o[14], lsrc);
        uint32_t unsafe = 0;
        if (check)
          asm volatile("{\n.reg .pred p, r;\nsetp.ge.f32 p, %1, 0f1F800000;\nsetp.le.and.f32 p, %2, 0f5F800000, p;\n"
                       "bar.red.and.pred r, %3, 128, p;\nselp.u32 %0, %4, 1, r;\n}"
                       : "=r"(unsafe) : "f"(fmin_nan(sum0, sum1)), "f"(fmax_nan(sum0, sum1)), "r"(4 + w), "r"(reloaded) : "memory");
        const float l0 = rcp(sum0), l1 = rcp(sum1);
        uint32_t u[8];
#pragma unroll
        for (int j = 0; j < 4; j++) {
          u[j] = pack(o[4 * j] * l0, o[4 * j + 1] * l0);
          u[4 + j] = pack(o[4 * j + 2] * l1, o[4 * j + 3] * l1);
        }
        const int xsrc = (lane & 28) | (2 * hh + (q >> 1));
        const uint32_t x0 = __shfl_sync(0xffffffffu, u[3], xsrc), x1 = __shfl_sync(0xffffffffu, u[7], xsrc), ps = 0x7610 + (q & 1) * 0x22;
        st_ll_if(!unsafe, op + 65536 * hh, u[0], u[4], u[1], tag_lo(u[5], otag));
        st_ll_if(!unsafe, op + 65536 * hh + 32, __byte_perm(x0, otag, ps), __byte_perm(x1, u[5], ps), u[2], u[6]);
        mbar_arrive_if(hh == 0 && !unsafe && lane == 0, bar(B_U0));
        TSH(w, 15 + 4 * hh, 15);
        return __any_sync(0xffffffffu, unsafe);
      };
      int redo_from;
      bool use_max = true;
      pin<8>(qa); pin<8>(qb);
      scores_a(qa, 0); scores_b(qa, 0);
      if (w) mbar_wait_tma(bar(B_E));
      wg_wait0();
      pin<96>(s + 32);
      TSH(w, 13, 13);
      softmax_pv(0, false, 0.f, 0.f, true);
      scores_a(qb, 1);
      const bool bad0 = finish(0, true, reload);
      scores_b(qb, 1);
      if (bad0) {
        wg_wait0();
        pin<96>(s + 32);
        redo_from = 0;
        use_max = !__any_sync(0xffffffffu, reload);
      } else {
        mbar_wait_tma(bar(B_E + 1 + w));
        wg_wait0();
        pin<96>(s + 32);
        TSH(w, 17, 13);
        softmax_pv(1, false, 0.f, 0.f, w == 0);
        redo_from = finish(1, true, 0) ? 1 : 2;
      }
      int handed = redo_from;
#pragma unroll 1
      for (int hh = redo_from; hh < 2;) {
        if (hh) {
#pragma unroll
          for (int i = 0; i < 8; i++) qa[i] = qb[i];
        }
        pin<8>(qa);
        scores_a(qa, hh); scores_b(qa, hh);
        wg_wait0();
        pin<96>(s + 32);
        float m0 = 0.f, m1 = 0.f;
        if (use_max) {
          float m2 = fmaxf(sd[4], sd[5]), m3 = fmaxf(sd[6], sd[7]);
          m0 = fmaxf(sd[0], sd[1]); m1 = fmaxf(sd[2], sd[3]);
          acc_max<24>(sd + 8, m0, m1, m2, m3);
          acc_max<96>(s + 32, m0, m1, m2, m3);
          m0 = fmaxf(m0, m2); m1 = fmaxf(m1, m3);
          m0 = fmaxf(m0, shfl_x(m0, 1)); m1 = fmaxf(m1, shfl_x(m1, 1));
          m0 = fmaxf(m0, shfl_x(m0, 2)); m1 = fmaxf(m1, shfl_x(m1, 2));
        }
        softmax_pv(hh, true, m0, m1, hh > handed && w == 0);
        handed = hh;
        if (finish(hh, !use_max, 0)) use_max = true;
        else hh++;
      }
    }
    const uint32_t o_sp = OFF(o[1][2 * m + w][lane & 7][wi][1][31]), a_os = sb + 1024 * wi + 16 * lane;
    int spins = 0;
    uint32_t redo;
#pragma unroll 1
    do {
      uint4 v[32];
      TSB(w, 2);
#pragma unroll
      for (int i = 12; i < 16; i++) v[i] = ld_ll(ip + 256 * (i >> 1) + 32 * (i & 1));
      const uint32_t* sp = (const uint32_t*)(scb + o_sp);
      const uint64_t db = mkdesc(__shfl_sync(0xffffffffu, sb + (g & 1) * 16, 0));
      if (spins == 0) {
        const uint32_t a0 = a_os + (w ? 40960 : R_V), a1 = a_os + (w ? 40960 : 16384);
        mbar_wait(bar(B_OS0 + w));
        static_for<0, 12>([&](auto I) { constexpr int i = decltype(I)::v; v[i] = lds128i<4096 * (i >> 1) + 512 * (i & 1)>(i < 8 ? a0 : a1); });
      } else {
#pragma unroll
        for (int i = 0; i < 12; i++) v[i] = ld_ll(ip + 256 * (i >> 1) + 32 * (i & 1));
      }
      uint32_t bad = 0, bad2 = 0;
#pragma unroll
      for (int i = 0; i < 16; i += 2) { bad |= v[i].w ^ otag; bad2 |= v[i + 1].x ^ otag; }
      bad = keep(bad | bad2); bad2 = 0;
#pragma unroll 1
      while (__any_sync(0xffffffffu, (ld_relaxed(sp) ^ otag) > 0xffffu) && ++spins < SPIN_LIMIT) {}
      TS(w, 12);
#pragma unroll
      for (int i = 0; i < 16; i++) v[16 + i] = ld_ll(ip + 65536 + 256 * (i >> 1) + 32 * (i & 1));
      TSB(w, 3);
      mbar_wait(bar(B_WO));
      TSB(w, 4);
#pragma unroll
      for (int i = 0; i < 16; i++) {
        const int st = i >> 3, gg = i & 7, mo = (st ? R_M1 : R_M0) + gg * 1024, ma = R_Q + st * 24576 + gg * 3072;
        uint4* u = v + 2 * i;
        if (i == 0 || i == 8) wg_fence();
        wg_n56_t(hv, u[0].x, u[0].y, u[0].z, u[0].w, db + ma / 16, i > 0);
        wg_n56_t(hv, u[1].x, u[1].y, u[1].z, u[1].w, db + mo / 16 + ((uint64_t)((ma + 1024 - mo) / 16) << 32), 1);
        if (i == 7) TSB(w, 5);
        if (i == 8) TSB(w, 6);
      }
      TS(w, 20);
      wg_commit();
      mbar_wait(bar(B_XS));
      const uint32_t a_xs = sb + X_SL + (16 * warp + (lane & 7)) * 128 + ((((lane >> 3) + (g & 1)) ^ lane) & 7) * 16;
      o_so = keep(OFF(stats[tile][g][r8])); o_si = keep(OFF(stats[tile][4 * (q & 1)][rloc]));
      o_cp = keep(OFF(crow[2 * tile][0][g][q])); inv_tok = keep(2 * (2047 - row0 - rloc));
      ldsm4(a_xs, xs); ldsm4(a_xs ^ 64, xs + 4); ldsm4(a_xs + 1024, xs + 8); ldsm4((a_xs ^ 64) + 1024, xs + 12);
#pragma unroll
      for (int j = 0; j < 7; j++) bw[j] = sel(r8 == 0, 0x3f803f80u, ((const volatile uint32_t*)(smem + R_WR))[4 * j + q]);
      wsum = ((const volatile float*)(smem + R_WR))[28];
#pragma unroll
      for (int i = 16; i < 32; i += 2) { bad |= v[i].w ^ otag; bad2 |= v[i + 1].x ^ otag; }
      asm volatile("{\n.reg .pred p, r;\nsetp.gt.u32 p, %1, 0xffff;\nbar.red.or.pred r, %2, 128, p;\nselp.u32 %0, 1, 0, r;\n}"
                   : "=r"(redo) : "r"(bad | bad2), "r"(4 + w) : "memory");
      wg_wait0();
      pin<28>(hv);
    } while (redo && ++spins < SPIN_LIMIT);
  }
  TS(w, 21);

  uint32_t hk[14], nk[14];
  uint32_t wa[28], wb[16];
  {
#pragma unroll
    for (int j = 0; j < 7; j++) {
      hk[2 * j] = add_bf2(xs[j], pack(hv[4 * j], hv[4 * j + 1]));
      hk[2 * j + 1] = add_bf2(xs[8 + j], pack(hv[4 * j + 2], hv[4 * j + 3]));
    }
    float c[6][4];
#pragma unroll
    for (int i = 0; i < 24; i++) c[i >> 2][i & 3] = 0.f;
#pragma unroll
    for (int j = 0; j < 7; j++) {
      mma1688(c[j & 1], hk[2 * j], hk[2 * j + 1], bw[j]);
      mma1688(c[2 + (j & 1)], hk[2 * j], hk[2 * j + 1], hk[2 * j]);
      mma1688(c[4 + (j & 1)], hk[2 * j], hk[2 * j + 1], hk[2 * j + 1]);
    }
    const float q0 = __shfl_sync(0xffffffffu, bsel ? c[2][1] + c[3][1] : c[2][0] + c[3][0], dsrc);
    const float q1 = __shfl_sync(0xffffffffu, bsel ? c[4][3] + c[5][3] : c[4][2] + c[5][2], dsrc);
    st_ll_if(q == 0, scb + o_so, __float_as_uint(c[0][0] + c[1][0]), __float_as_uint(c[0][1] + c[1][1]), __float_as_uint(q0), epoch);
    st_ll_if(q == 0, scb + o_so + 128, __float_as_uint(c[0][2] + c[1][2]), __float_as_uint(c[0][3] + c[1][3]), __float_as_uint(q1), epoch);
    TSB(w, 7);
    {
      o_rp = keep(OFF(rec[g][tile]));
      a_ci = keep(sb + SMALL + 4096 + 1024 * bsel + 256 * (warp >> 1) + 16 * q);
      o_pp = keep(OFF(part[16 * warp + 4 * q + (r8 >> 1)][cta][r8 & 1]));
      o_gp = keep(OFF(part[cta][lane >> 1][lane & 1]));
      f1w = keep(sb + SMALL + 4 * (64 + 32 * warp + 16 * (q & 1) + 4 * (r8 >> 1) + (r8 & 1) + (q & 2)));
      f1r = keep(sb + SMALL + 4 * (64 + 16 * bsel + 4 * q));
      const uint32_t kr = (lane & 7) + 8 * (lane >> 4), ch = (lane >> 3) & 1;
      a_wa = keep(sb + R_F + (warp & 1) * 14336 + (112 * (warp >> 1) + kr) * 32 + (ch ^ ((lane >> 2) & 1)) * 16);
      a_wb = keep(sb + R_F + 28672 + 2048 * min(warp, 6) + kr * 128 + (ch ^ (lane & 7)) * 16);
      a_st = keep(sb + X_SL + 2048 * warp + (lane & 7) * 112 + (lane >> 3) * 16);
    }
#pragma unroll
    for (int j = 0; j < 7; j++) {
      hv[4 * j] = lo_f(hk[2 * j]); hv[4 * j + 1] = hi_f(hk[2 * j]); hv[4 * j + 2] = lo_f(hk[2 * j + 1]); hv[4 * j + 3] = hi_f(hk[2 * j + 1]);
    }
    pin<28>(hv);
    uint4 u[4];
    int spins = 0;
#pragma unroll 1
    do {
#pragma unroll
      for (int i = 0; i < 4; i++) u[i] = ld_ll(scb + o_si + 256 * i);
    } while (__any_sync(0xffffffffu, (((u[0].w ^ epoch) | (u[1].w ^ epoch)) | ((u[2].w ^ epoch) | (u[3].w ^ epoch))) != 0) && ++spins < SPIN_LIMIT);
    TS(w, 22);
    float s1 = (__uint_as_float(u[0].x) + __uint_as_float(u[1].x)) + (__uint_as_float(u[2].x) + __uint_as_float(u[3].x));
    float s3 = (__uint_as_float(u[0].y) + __uint_as_float(u[1].y)) + (__uint_as_float(u[2].y) + __uint_as_float(u[3].y));
    float s2 = (__uint_as_float(u[0].z) + __uint_as_float(u[1].z)) + (__uint_as_float(u[2].z) + __uint_as_float(u[3].z));
    s1 += shfl_x(s1, 1); s2 += shfl_x(s2, 1); s3 += shfl_x(s3, 1);
    const float mu = s1 * (1.f / D_);
    float rs;
    asm("rsqrt.approx.ftz.f32 %0, %1;" : "=f"(rs) : "f"(fmaxf(fmaf(s2, 1.f / D_, -mu * mu), 0.f) + 1e-5f));
    uint32_t k1, k2;
    top2(to_key(rs * fmaf(-mu, wsum, s3), inv_tok), k1, k2);
    st_ll_if(lane == 0, scb + o_rp, k1, k2 | 1, 0, epoch);
    mbar_arrive_if(lane == 0, bar(B_S1));
    const bool up = q >= 2;
    const float nb = -mu * rs;
    const float rsx = shfl_x(rs, 2), nbx = shfl_x(nb, 2);
    const float rs0 = up ? rsx : rs, rs1 = up ? rs : rsx, nb0 = up ? nbx : nb, nb1 = up ? nb : nbx;
#pragma unroll
    for (int j = 0; j < 7; j++) {
      nk[2 * j] = pack(fmaf(hv[4 * j], rs0, nb0), fmaf(hv[4 * j + 1], rs0, nb0));
      nk[2 * j + 1] = pack(fmaf(hv[4 * j + 2], rs1, nb1), fmaf(hv[4 * j + 3], rs1, nb1));
    }
    const uint32_t d1 = key_token(k1) & 15, d2 = key_token(k2) & 15;
#pragma unroll
    for (int a = 0; a < 2; a++) {
#pragma unroll
      for (int h = 0; h < 2; h++) {
        const uint32_t* k = (a ? hk : nk) + h;
        const bool on = d1 == r8 + 8 * h || d2 == r8 + 8 * h;
        char* p = scb + o_cp + (d2 == r8 + 8 * h ? 2048 : 0) + 1024 * a;
        st_ll_if(on, p, k[0], k[2], k[4], tag_lo(k[6], tag_hi));
        st_ll_if(on, p + 64, k[8], k[10], k[12], tag_up(k[6], tag_hi));
      }
    }
  }
  TS(w, 23);
  {
    if (cta < NFFN) mbar_wait(bar(B_FF));
#pragma unroll
    for (int i = 0; i < 7; i++) ldsm4t(a_wa + 512 * i, wa + 4 * i);
#pragma unroll
    for (int i = 0; i < 4; i++) ldsm4t(a_wb ^ (32 * i), wb + 4 * i);
    const uint32_t base = a_st;
    __syncwarp();
    uint32_t k[14];
#pragma unroll
    for (int j = 0; j < 14; j++) k[j] = add_bf2(hk[j], nk[j]);
    stsm4(base, k[0], k[2], k[4], k[6]);
    stsm4(base + 896, k[1], k[3], k[5], k[7]);
    stsm4(base + 48, k[6], k[8], k[10], k[12]);
    stsm4(base + 944, k[7], k[9], k[11], k[13]);
    __syncwarp();
    if (cta >= NFFN) { if (lane == 0) mbar_arrive(bar(B_WIN)); }
    else {
      TSB(w, 8);
      mbar_wait(bar(B_ROW));
      TS(w, 24);
      uint4 t[4];
#pragma unroll
      for (int i = 0; i < 4; i++) { const float4 f = lds128(a_ci + 64 * i); t[i] = make_uint4(__float_as_uint(f.x), __float_as_uint(f.y), __float_as_uint(f.z), __float_as_uint(f.w)); }
      const uint32_t kk[14] = {t[0].x, t[0].y, t[0].z, untag(t[0].w, t[1].w), t[1].x, t[1].y, t[1].z,
                               t[2].x, t[2].y, t[2].z, untag(t[2].w, t[3].w), t[3].x, t[3].y, t[3].z};
      float c[4] = {0.f, 0.f, 0.f, 0.f}, d[4] = {0.f, 0.f, 0.f, 0.f}, c2[4] = {0.f, 0.f, 0.f, 0.f}, d2[4] = {0.f, 0.f, 0.f, 0.f};
#pragma unroll
      for (int i = 0; i < 7; i++) mma16816((i & 2) ? ((i & 1) ? d2 : c2) : ((i & 1) ? d : c), wa[4 * i], wa[4 * i + 1], wa[4 * i + 2], wa[4 * i + 3], kk[2 * i], kk[2 * i + 1]);
#pragma unroll
      for (int i = 0; i < 4; i++) { c[i] += c2[i]; d[i] += d2[i]; }
      const float z = self(q & 2, self(q & 1, c[3], c[2]) + self(q & 1, d[3], d[2]), self(q & 1, c[1], c[0]) + self(q & 1, d[1], d[0]));
      asm volatile("st.shared.f32 [%0], %1;" ::"r"(f1w), "f"(z) : "memory");
      __syncwarp();
      if (lane == 0) mbar_arrive(bar(B_S2));
      if (warp < 7) {
        mbar_wait(bar(B_S2));
        TS(w, 25);
        float4 pa[8];
#pragma unroll
        for (int k = 0; k < 8; k++) pa[k] = lds128(f1r + 128 * k);
        float4 gs = pa[0], us = pa[1];
#pragma unroll
        for (int k = 1; k < 4; k++) {
          const float4 a = pa[2 * k], b = pa[2 * k + 1];
          gs.x += a.x; gs.y += a.y; gs.z += a.z; gs.w += a.w; us.x += b.x; us.y += b.y; us.z += b.z; us.w += b.w;
        }
        const uint32_t g0 = pack(gs.x, gs.y), g1 = pack(gs.z, gs.w), u0 = pack(us.x, us.y), u1 = pack(us.z, us.w);
        auto silu = [](float v) { return v * rcp(1.f + ex2(-1.4426950408889634f * v)); };
        const uint32_t b0 = mul_bf2(pack(silu(lo_f(g0)), silu(hi_f(g0))), u0), b1 = mul_bf2(pack(silu(lo_f(g1)), silu(hi_f(g1))), u1);
        float e[4][4];
#pragma unroll
        for (int i = 0; i < 4; i++) {
          e[i][0] = e[i][1] = e[i][2] = e[i][3] = 0.f;
          mma16816(e[i], wb[4 * i], wb[4 * i + 1], wb[4 * i + 2], wb[4 * i + 3], b0, b1);
        }
        float y[4];
#pragma unroll
        for (int i = 0; i < 4; i++) y[i] = (q & 2) ? ((q & 1) ? e[3][i] : e[2][i]) : ((q & 1) ? e[1][i] : e[0][i]);
        st_ll(scb + o_pp, __float_as_uint(y[0]), __float_as_uint(y[1]), __float_as_uint(y[2]), (__float_as_uint(y[3]) & ~15u) | (epoch & 15u));
      }
      TS(w, 26);
      if (lane == 0) mbar_arrive(bar(B_WIN));
    }
  }
  if (cta < NFFN && warp == 7) {
    mbar_wait(bar(B_FIN));
    const float4 fin = lds128(sb + SMALL + 2048 + 16 * (lane & 7));
    __nv_bfloat16* outp = P.out + __float_as_uint(fin.w);
    mbar_wait(bar(B_WIN));
    int spins = 0;
    uint4 pu[7];
    uint32_t bad;
#pragma unroll 1
    do {
      bad = 0;
#pragma unroll
      for (int i = 0; i < 7; i++) pu[i] = ld_ll(scb + o_gp + 512 * i);
#pragma unroll
      for (int i = 0; i < 7; i++) bad |= pu[i].w ^ epoch;
    } while (__any_sync(0xffffffffu, (bad & 15u) != 0) && ++spins < SPIN_LIMIT);
    float y[4];
#pragma unroll
    for (int c = 0; c < 4; c++) {
      float t[7];
#pragma unroll
      for (int i = 0; i < 7; i++) t[i] = __uint_as_float(c == 0 ? pu[i].x : (c == 1 ? pu[i].y : (c == 2 ? pu[i].z : pu[i].w & ~15u)));
      y[c] = ((t[0] + t[1]) + (t[2] + t[3])) + ((t[4] + t[5]) + t[6]);
    }
    const bool s1 = lane & 2, s2 = lane & 4;
    const float z0 = (s1 ? y[1] : y[0]) + shfl_x(s1 ? y[0] : y[1], 2), z2 = (s1 ? y[3] : y[2]) + shfl_x(s1 ? y[2] : y[3], 2);
    float z = (s2 ? z2 : z0) + shfl_x(s2 ? z0 : z2, 4);
    z += shfl_x(z, 8); z += shfl_x(z, 16);
    if (lane < 8) *outp = __float2bfloat16_rn(fin.y + rbf(fin.x + rbf(rbf(z) * fin.z)));
    if (cta == 0 && lane == 0) st_relaxed(&sc->epoch[0], epoch);
  }
  TSDUMP();
}

typedef CUresult (*EncodeFn)(CUtensorMap*, CUtensorMapDataType, cuuint32_t, void*, const cuuint64_t*, const cuuint64_t*,
                             const cuuint32_t*, const cuuint32_t*, CUtensorMapInterleave, CUtensorMapSwizzle,
                             CUtensorMapL2promotion, CUtensorMapFloatOOBfill);

CUtensorMap make_map(EncodeFn enc, const void* p, int rank, const cuuint64_t* dims, const cuuint64_t* strides,
                     const cuuint32_t* box, CUtensorMapSwizzle sw) {
  CUtensorMap m;
  const cuuint32_t es[5] = {1, 1, 1, 1, 1};
  enc(&m, CU_TENSOR_MAP_DATA_TYPE_BFLOAT16, rank, const_cast<void*>(p), dims, strides, box, es, CU_TENSOR_MAP_INTERLEAVE_NONE, sw,
      CU_TENSOR_MAP_L2_PROMOTION_NONE, CU_TENSOR_MAP_FLOAT_OOB_FILL_NONE);
  return m;
}
CUtensorMap make_map2(EncodeFn enc, const void* p, int cols, int rows, int bc, int br, CUtensorMapSwizzle sw) {
  const cuuint64_t dims[2] = {(cuuint64_t)cols, (cuuint64_t)rows}, strides[1] = {(cuuint64_t)cols * 2};
  const cuuint32_t box[2] = {(cuuint32_t)bc, (cuuint32_t)br};
  return make_map(enc, p, 2, dims, strides, box, sw);
}

}

extern "C" void kernel_launch(void* const* d_in, const int* in_sizes, int n_in, void* d_out, int out_size) {
  (void)in_sizes; (void)n_in; (void)out_size;
  static EncodeFn enc = nullptr;
  static Scratch* sc = nullptr;
  if (!enc) {
    void* fn = nullptr;
    cudaDriverEntryPointQueryResult qr;
    cudaGetDriverEntryPoint("cuTensorMapEncodeTiled", &fn, cudaEnableDefault, &qr);
    enc = (EncodeFn)fn;
    cudaGetSymbolAddress((void**)&sc, g_sc);
    cudaFuncSetAttribute(fused_block_kernel, cudaFuncAttributeMaxDynamicSharedMemorySize, SMEM_BYTES);
  }
  Params P;
  P.x = (const __nv_bfloat16*)d_in[0];  P.wqkv = (const __nv_bfloat16*)d_in[1];  P.wo = (const __nv_bfloat16*)d_in[2]; P.wr = (const __nv_bfloat16*)d_in[4];
  P.wg = (const __nv_bfloat16*)d_in[5]; P.wu = (const __nv_bfloat16*)d_in[6]; P.wd = (const __nv_bfloat16*)d_in[7];
  P.out = (__nv_bfloat16*)d_out; P.sc = sc;
  const CUtensorMap tm_w = make_map2(enc, d_in[1], 3 * D_, D_, 64, 112, CU_TENSOR_MAP_SWIZZLE_128B);
  const cuuint64_t od3[3] = {448, 56, 8}, os3[2] = {896, 56 * 896};
  const cuuint32_t ob3[3] = {64, 24, 8};
  const CUtensorMap tm_wo = make_map(enc, P.wo, 3, od3, os3, ob3, CU_TENSOR_MAP_SWIZZLE_128B);
  const CUtensorMap tm_x = make_map2(enc, P.x, D_, S_, 64, 128, CU_TENSOR_MAP_SWIZZLE_128B);
  const cuuint64_t dd3[3] = {64, F_, 7}, ds3[2] = {896, 128};
  const cuuint32_t db3[3] = {64, 16, 7};
  const CUtensorMap tm_d = make_map(enc, P.wd, 3, dd3, ds3, db3, CU_TENSOR_MAP_SWIZZLE_128B);
  const CUtensorMap tm_g = make_map2(enc, P.wg, F_, D_, 16, 224, CU_TENSOR_MAP_SWIZZLE_32B);
  const CUtensorMap tm_u = make_map2(enc, P.wu, F_, D_, 16, 224, CU_TENSOR_MAP_SWIZZLE_32B);
  fused_block_kernel<<<NCTA, NTHREADS, SMEM_BYTES, cudaStreamPerThread>>>(P, tm_x, tm_w, tm_wo, tm_d, tm_g, tm_u);
}
```
